```python
import torch

def _softmax(x, axis=-1):
    return torch.softmax(x, dim=axis)

def _gelu(x):
    return torch.nn.functional.gelu(x, approximate='tanh')

def _silu(x):
    return torch.nn.functional.silu(x)

def _sigmoid(x):
    return torch.sigmoid(x)

def _layernorm(x, axis=-1, eps=1e-05):
    m = x.mean(dim=axis, keepdim=True)
    v = x.var(dim=axis, keepdim=True, unbiased=False)
    return (x - m) / torch.sqrt(v + eps)

def _scatter_add(tgt, idx, src, axis=0):
    return tgt.clone().index_add_(axis, idx, src)

def _segment_sum(src, seg, n):
    out = torch.zeros((n,) + src.shape[1:], dtype=src.dtype)
    return out.index_add_(0, seg, src)

def _pad(x, pw):
    flat = tuple((v for pair in reversed(pw) for v in pair))
    return torch.nn.functional.pad(x, flat)
kernel_name = 'adaLN_cond__gqa_block_cached__swiglu_ffn__decode'

def setup_inputs():

    _w = lambda a: (lambda t: t.to(torch.bfloat16) if t.is_floating_point() else t)(torch.as_tensor(a))

    def _A_setup():
        B, Sq, D = (1, 1, 576)
        Hq, Hkv, Sk, Dh = (32, 16, 65536, 128)
        assert Hq % Hkv == 0, (Hq, Hkv)
        return {'x': _w((lambda *s: torch.randn(*s, dtype=torch.bfloat16) * 0.05)(B, Sq, D)), 'k_cache': _w((lambda *s: torch.randn(*s, dtype=torch.bfloat16) * 3.2)(B, Hkv, Sk, Dh)), 'v_cache': _w((lambda *s: torch.randn(*s, dtype=torch.bfloat16) * 0.4)(B, Hkv, Sk, Dh)), 'wq': _w((lambda *s: torch.randn(*s, dtype=torch.bfloat16) * 3.2)(D, Hq * Dh) * D ** (-0.5)), 'wo': _w((lambda *s: torch.randn(*s, dtype=torch.bfloat16) * 0.4)(Hq * Dh, D) * (Hq * Dh) ** (-0.5))}
    _A_in = _A_setup()

    def _B_setup():
        B, S, D, F = (1, 1, 576, 4608)
        return {'x': _w((lambda *s: torch.randn(*s, dtype=torch.bfloat16) * 0.05)(B, S, D)), 'w_gate': _w((lambda *s: torch.randn(*s, dtype=torch.bfloat16) * 0.05)(D, F)), 'w_up': _w((lambda *s: torch.randn(*s, dtype=torch.bfloat16) * 0.05)(D, F)), 'w_down': _w((lambda *s: torch.randn(*s, dtype=torch.bfloat16) * 0.05)(F, D))}
    _B_in = _B_setup()
    return {'A_x': _A_in['x'], 'A_k_cache': _A_in['k_cache'], 'A_v_cache': _A_in['v_cache'], 'A_wq': _A_in['wq'], 'A_wo': _A_in['wo'], 'B_x': _B_in['x'], 'B_w_gate': _B_in['w_gate'], 'B_w_up': _B_in['w_up'], 'B_w_down': _B_in['w_down'], 'c': _w((lambda *s: torch.randn(*s, dtype=torch.bfloat16) * 0.2)(1, 576) * 8.0), 'w_mod': _w((lambda *s: torch.randn(*s, dtype=torch.bfloat16) * 0.2)(576, 6 * 576) * 576 ** (-0.5) * 8.0)}

def reference(A_x, A_k_cache, A_v_cache, A_wq, A_wo, B_x, B_w_gate, B_w_up, B_w_down, c, w_mod):

    def _A_ref(x, k_cache, v_cache, wq, wo):
        B, Sq, D = x.shape
        Hq, Dh = (32, 128)
        Hkv = k_cache.shape[1]
        rep = Hq // Hkv
        q = (lambda x, *d: x.permute(*d))((x @ wq).reshape(B, Sq, Hq, Dh), 0, 2, 1, 3)
        k = (lambda x, n, axis: torch.repeat_interleave(x, n, dim=axis))(k_cache, rep, axis=1)
        v = (lambda x, n, axis: torch.repeat_interleave(x, n, dim=axis))(v_cache, rep, axis=1)
        scores = torch.einsum('bhqd,bhkd->bhqk', q, k) * Dh ** (-0.5)
        p = _softmax(scores, axis=-1)
        o = torch.einsum('bhqk,bhkd->bhqd', p, v)
        return (lambda x, *d: x.permute(*d))(o, 0, 2, 1, 3).reshape(B, Sq, Hq * Dh) @ wo

    def _B_ref(x, w_gate, w_up, w_down):
        g = _silu(x @ w_gate)
        u = x @ w_up
        return g * u @ w_down
    x = A_x
    mod = (_silu(c) @ w_mod).reshape(c.shape[0], 6, 1, -1)
    sa, ca, ga, sb, cb, gb = (mod[:, 0].clone(), mod[:, 1].clone(), mod[:, 2].clone(), mod[:, 3].clone(), mod[:, 4].clone(), mod[:, 5].clone())
    h = _layernorm(x, axis=-1) * (1 + ca) + sa
    x = x + ga * _A_ref(h, A_k_cache, A_v_cache, A_wq, A_wo)
    h = _layernorm(x, axis=-1) * (1 + cb) + sb
    x = x + gb * _B_ref(h, B_w_gate, B_w_up, B_w_down)
    return x
```

```cpp
#include <cuda_runtime.h>
#include <cuda_bf16.h>
#include <cuda.h>
#include <stdint.h>

namespace {

constexpr int D_MODEL = 576;
constexpr int HKV = 16;
constexpr int SK = 65536;
constexpr int FF = 4608;
constexpr int TILE = 64;
constexpr int TPH = SK / TILE;
constexpr int NT = HKV * TPH;
constexpr int NSLOT = 4;
constexpr int SLOT_BYTES = TILE * 256;
constexpr int MAXG = 144;
constexpr int N_MOD_CTA = 108;
constexpr int N_Q_CTA = 128;
constexpr int N_JOB_CTA = 128;
constexpr int N_FFN_CTA = 116;
constexpr int N_FIN_CTA = 72;
constexpr int FCOLS = 40;
constexpr int WPITCH = 1168;

constexpr int NCONS = 128;
constexpr int NAUX = 288;
constexpr int NTHREADS = NCONS + 32 + NAUX;

constexpr int SM_RING = 0;
constexpr int SM_G = SM_RING + NSLOT * SLOT_BYTES;
constexpr int SM_GSZ = D_MODEL * FCOLS * 2;
constexpr int SM_D = SM_G + 2 * SM_GSZ;
constexpr int SM_Q = SM_D + FCOLS * WPITCH;
constexpr int SM_FB = SM_Q + 8192;
constexpr int SM_FML = SM_FB + 8192;
constexpr int SM_JOB = SM_FML + 128;
constexpr int SM_BAR = SM_JOB + 2048;
constexpr int SM_TOTAL = SM_BAR + 256;
constexpr int SM_PRE_VEC = SM_FB;
constexpr int SM_PRE_RED = SM_FB + 2304;
constexpr int SM_PRE_ST = SM_FB + 2304 + 1152;
constexpr int SM_T_YS = SM_RING;
constexpr int SM_T_X2 = SM_RING + 4608;
constexpr int SM_T_H2 = SM_T_X2 + 2304;
constexpr int SM_T_RED = SM_T_H2 + 1152;
constexpr int SM_T_ST = SM_T_RED + 2880;
constexpr int SM_T_ACT = SM_T_ST + 128;
constexpr int SM_T_FIN = SM_T_ACT + 128;

constexpr int B_FULL = 0;
constexpr int B_EMPTY = 64;
constexpr int B_QRDY = 128;
constexpr int B_JOB = 136;
constexpr int B_WO = 144;
constexpr int B_GU = 152;
constexpr int B_DOWN = 160;
constexpr int B_TILE = 192;

constexpr unsigned SPIN_MAX = 1u << 21;

struct Scratch {
    uint32_t mod[3456];
    uint32_t q[4096];
    uint32_t po[HKV][8][MAXG][32];
    uint32_t pml[HKV][2][MAXG][2];
    uint32_t y[HKV][8][D_MODEL];
    uint32_t y2[N_FFN_CTA][D_MODEL];
    uint32_t ctr[32];
    uint32_t epoch[32];
};
__device__ __align__(128) Scratch g_s;

#define TS(i) do { } while (0)

__device__ __forceinline__ uint32_t smem_u32(const void* p) { return (uint32_t)__cvta_generic_to_shared(p); }
__device__ __forceinline__ void mbar_init(uint32_t bar, uint32_t cnt) {
    asm volatile("mbarrier.init.shared::cta.b64 [%0], %1;" ::"r"(bar), "r"(cnt) : "memory");
}
__device__ __forceinline__ void mbar_expect_tx(uint32_t bar, uint32_t bytes) {
    asm volatile("mbarrier.arrive.expect_tx.shared::cta.b64 _, [%0], %1;" ::"r"(bar), "r"(bytes) : "memory");
}
__device__ __forceinline__ void mbar_arrive(uint32_t bar) {
    asm volatile("mbarrier.arrive.shared::cta.b64 _, [%0];" ::"r"(bar) : "memory");
}
__device__ __forceinline__ bool mbar_try(uint32_t bar, uint32_t parity) {
    uint32_t ok;
    asm volatile("{\n.reg .pred p;\nmbarrier.try_wait.parity.shared::cta.b64 p, [%1], %2;\nselp.u32 %0, 1, 0, p;\n}"
                 : "=r"(ok) : "r"(bar), "r"(parity) : "memory");
    return ok != 0;
}
__device__ __forceinline__ void mbar_wait(uint32_t bar, uint32_t parity) {
    if (mbar_try(bar, parity)) return;
    const long long t0 = clock64();
    while (!mbar_try(bar, parity)) {
        if (clock64() - t0 > (1ll << 31)) __trap();
    }
}
__device__ __forceinline__ void bar_sync(int id, int n) { asm volatile("bar.sync %0, %1;" ::"r"(id), "r"(n) : "memory"); }

__device__ __forceinline__ void tma3d(uint32_t dst, const CUtensorMap* m, int c2, uint32_t bar) {
    asm volatile("cp.async.bulk.tensor.3d.shared::cluster.global.mbarrier::complete_tx::bytes [%0], [%1, {%3, %3, %4}], [%2];"
                 ::"r"(dst), "l"(m), "r"(bar), "r"(0), "r"(c2) : "memory");
}
__device__ __forceinline__ void tma2d(uint32_t dst, const CUtensorMap* m, int c0, int c1, uint32_t bar) {
    asm volatile("cp.async.bulk.tensor.2d.shared::cluster.global.mbarrier::complete_tx::bytes [%0], [%1, {%3, %4}], [%2];"
                 ::"r"(dst), "l"(m), "r"(bar), "r"(c0), "r"(c1) : "memory");
}
__device__ __forceinline__ void bulk1d(uint32_t dst, const void* src, uint32_t bytes, uint32_t bar) {
    asm volatile("cp.async.bulk.shared::cluster.global.mbarrier::complete_tx::bytes [%0], [%1], %2, [%3];"
                 ::"r"(dst), "l"(src), "r"(bytes), "r"(bar) : "memory");
}
__device__ __forceinline__ void ldsm4(uint32_t (&r)[4], uint32_t addr) {
    asm volatile("ldmatrix.sync.aligned.m8n8.x4.shared.b16 {%0,%1,%2,%3}, [%4];"
                 : "=r"(r[0]), "=r"(r[1]), "=r"(r[2]), "=r"(r[3]) : "r"(addr) : "memory");
}
__device__ __forceinline__ void ldsm4t(uint32_t (&r)[4], uint32_t addr) {
    asm volatile("ldmatrix.sync.aligned.m8n8.x4.trans.shared.b16 {%0,%1,%2,%3}, [%4];"
                 : "=r"(r[0]), "=r"(r[1]), "=r"(r[2]), "=r"(r[3]) : "r"(addr) : "memory");
}
__device__ __forceinline__ void ldsm1t(uint32_t& r, uint32_t addr) {
    asm volatile("ldmatrix.sync.aligned.m8n8.x1.trans.shared.b16 {%0}, [%1];" : "=r"(r) : "r"(addr) : "memory");
}
__device__ __forceinline__ void mma16816(float (&c)[4], uint32_t a0, uint32_t a1, uint32_t a2, uint32_t a3, uint32_t b0, uint32_t b1) {
    asm volatile("mma.sync.aligned.m16n8k16.row.col.f32.bf16.bf16.f32 {%0,%1,%2,%3}, {%4,%5,%6,%7}, {%8,%9}, {%0,%1,%2,%3};"
                 : "+f"(c[0]), "+f"(c[1]), "+f"(c[2]), "+f"(c[3])
                 : "r"(a0), "r"(a1), "r"(a2), "r"(a3), "r"(b0), "r"(b1));
}
__device__ __forceinline__ void mma1688(float (&c)[4], uint32_t a0, uint32_t a1, uint32_t b0) {
    asm volatile("mma.sync.aligned.m16n8k8.row.col.f32.bf16.bf16.f32 {%0,%1,%2,%3}, {%4,%5}, {%6}, {%0,%1,%2,%3};"
                 : "+f"(c[0]), "+f"(c[1]), "+f"(c[2]), "+f"(c[3])
                 : "r"(a0), "r"(a1), "r"(b0));
}
__device__ __forceinline__ uint32_t movmatrix_t(uint32_t a) {
    uint32_t d;
    asm volatile("movmatrix.sync.aligned.m8n8.trans.b16 %0, %1;" : "=r"(d) : "r"(a));
    return d;
}
__device__ __forceinline__ uint32_t pack_bf16(float lo, float hi) {
    uint32_t d;
    asm("cvt.rn.bf16x2.f32 %0, %1, %2;" : "=r"(d) : "f"(hi), "f"(lo));
    return d;
}
__device__ __forceinline__ float bf_lo(uint32_t v) { return __uint_as_float(v << 16); }
__device__ __forceinline__ float bf_hi(uint32_t v) { return __uint_as_float(v & 0xffff0000u); }
__device__ __forceinline__ float bfr(float x) { return bf_lo(pack_bf16(x, 0.f)); }
__device__ __forceinline__ uint32_t max_bf16x2(uint32_t a, uint32_t b) {
    uint32_t d;
    asm("max.bf16x2 %0, %1, %2;" : "=r"(d) : "r"(a), "r"(b));
    return d;
}
__device__ __forceinline__ float ex2(float x) {
    float y;
    asm("ex2.approx.ftz.f32 %0, %1;" : "=f"(y) : "f"(x));
    return y;
}
__device__ __forceinline__ float silu_f(float x) { return __fdividef(x, 1.0f + __expf(-x)); }

__device__ __forceinline__ uint4 ld_poll4(const uint32_t* p) {
    uint4 v;
    asm volatile("ld.relaxed.gpu.global.v4.u32 {%0,%1,%2,%3}, [%4];" : "=r"(v.x), "=r"(v.y), "=r"(v.z), "=r"(v.w) : "l"(p) : "memory");
    return v;
}
__device__ __forceinline__ uint2 ld_poll2(const uint32_t* p) {
    uint2 v;
    asm volatile("ld.relaxed.gpu.global.v2.u32 {%0,%1}, [%2];" : "=r"(v.x), "=r"(v.y) : "l"(p) : "memory");
    return v;
}
__device__ __forceinline__ uint32_t ld_poll1(const uint32_t* p) {
    uint32_t v;
    asm volatile("ld.relaxed.gpu.global.u32 %0, [%1];" : "=r"(v) : "l"(p) : "memory");
    return v;
}
__device__ __forceinline__ void st_pub1(uint32_t* p, uint32_t a) {
    asm volatile("st.relaxed.gpu.global.u32 [%0], %1;" ::"l"(p), "r"(a) : "memory");
}
__device__ __forceinline__ void st_pub2(uint32_t* p, uint32_t a, uint32_t b) {
    asm volatile("st.relaxed.gpu.global.v2.u32 [%0], {%1,%2};" ::"l"(p), "r"(a), "r"(b) : "memory");
}
__device__ __forceinline__ uint32_t tagf(float v, uint32_t tag) { return (__float_as_uint(v) & ~3u) | tag; }
__device__ __forceinline__ uint32_t bad4(const uint4& v, uint32_t tag) { return ((v.x ^ tag) | (v.y ^ tag) | (v.z ^ tag) | (v.w ^ tag)) & 3u; }
__device__ __forceinline__ uint32_t bad2(const uint2& v, uint32_t tag) { return ((v.x ^ tag) | (v.y ^ tag)) & 3u; }
__device__ __forceinline__ float untag_bf(uint32_t v) { return __uint_as_float(v & 0xffff0000u); }

__device__ __forceinline__ uint4 ldg_nc4(const void* p) {
    uint4 v;
    asm volatile("ld.global.nc.L1::no_allocate.v4.u32 {%0,%1,%2,%3}, [%4];" : "=r"(v.x), "=r"(v.y), "=r"(v.z), "=r"(v.w) : "l"(p));
    return v;
}

constexpr float LOG2E = 1.4426950408889634f;
constexpr float QK_SCALE = 0.08838834764831845f;
constexpr uint32_t M_INIT = 0xFF7FFF7Fu;

__device__ __forceinline__ void gemv32_partial(const uint4 (&w)[8], const float* vec, float* red, int at) {
    const int rg = at >> 2, lane = at & 31, wa = at >> 5;
    float acc[8];
#pragma unroll
    for (int j = 0; j < 8; j++) acc[j] = 0.f;
#pragma unroll
    for (int i = 0; i < 8; i++) {
        const float v = vec[rg + 72 * i];
        acc[0] = fmaf(v, bf_lo(w[i].x), acc[0]); acc[1] = fmaf(v, bf_hi(w[i].x), acc[1]);
        acc[2] = fmaf(v, bf_lo(w[i].y), acc[2]); acc[3] = fmaf(v, bf_hi(w[i].y), acc[3]);
        acc[4] = fmaf(v, bf_lo(w[i].z), acc[4]); acc[5] = fmaf(v, bf_hi(w[i].z), acc[5]);
        acc[6] = fmaf(v, bf_lo(w[i].w), acc[6]); acc[7] = fmaf(v, bf_hi(w[i].w), acc[7]);
    }
    {
        const bool up = lane & 4;
#pragma unroll
        for (int j = 0; j < 4; j++) {
            const float send = up ? acc[j] : acc[j + 4];
            const float keep = up ? acc[j + 4] : acc[j];
            acc[j] = keep + __shfl_xor_sync(0xffffffffu, send, 4);
        }
    }
    {
        const bool up = lane & 8;
#pragma unroll
        for (int j = 0; j < 2; j++) {
            const float send = up ? acc[j] : acc[j + 2];
            const float keep = up ? acc[j + 2] : acc[j];
            acc[j] = keep + __shfl_xor_sync(0xffffffffu, send, 8);
        }
    }
    {
        const bool up = lane & 16;
        const float send = up ? acc[0] : acc[1];
        const float keep = up ? acc[1] : acc[0];
        acc[0] = keep + __shfl_xor_sync(0xffffffffu, send, 16);
    }
    const int col = (lane & 3) * 8 + ((lane & 4) ? 4 : 0) + ((lane & 8) ? 2 : 0) + ((lane & 16) ? 1 : 0);
    red[wa * 32 + col] = acc[0];
}

__device__ __forceinline__ void ln_stats(float x0, float x1, float* st, int at, float& mean_r, float& sd_r) {
    float mean = 0.5f * (x0 + x1);
    float dlt = x0 - x1;
    float m2 = 0.5f * dlt * dlt;
    float n = 2.f;
#pragma unroll
    for (int o = 1; o < 32; o <<= 1) {
        const float mo = __shfl_xor_sync(0xffffffffu, mean, o);
        const float m2o = __shfl_xor_sync(0xffffffffu, m2, o);
        const float d = mo - mean;
        m2 = m2 + m2o + d * d * (0.5f * n);
        mean = 0.5f * (mean + mo);
        n *= 2.f;
    }
    if ((at & 31) == 0) { st[(at >> 5) * 2] = mean; st[(at >> 5) * 2 + 1] = m2; }
    bar_sync(2, NAUX);
    float ms = 0.f, m2s = 0.f;
#pragma unroll
    for (int w = 0; w < 9; w++) { ms += st[2 * w]; m2s += st[2 * w + 1]; }
    const float mu = ms * (1.0f / 9.0f);
    float dd = 0.f;
#pragma unroll
    for (int w = 0; w < 9; w++) { const float d = st[2 * w] - mu; dd = fmaf(d, d, dd); }
    const float var = (m2s + 64.f * dd) * (1.0f / 576.0f);
    mean_r = bfr(mu);
    sd_r = bfr(sqrtf(bfr(bfr(var) + 1e-5f)));
}

__global__ void __launch_bounds__(NTHREADS, 1)
fused_kernel(const __grid_constant__ CUtensorMap tmK, const __grid_constant__ CUtensorMap tmV,
             const __grid_constant__ CUtensorMap tmG, const __grid_constant__ CUtensorMap tmU,
             const __nv_bfloat16* __restrict__ x_in, const __nv_bfloat16* __restrict__ wq,
             const __nv_bfloat16* __restrict__ wo, const __nv_bfloat16* __restrict__ wdown,
             const __nv_bfloat16* __restrict__ c_in, const __nv_bfloat16* __restrict__ wmod,
             __nv_bfloat16* __restrict__ out)
{
    extern __shared__ __align__(1024) uint8_t smem[];
    const uint32_t sb = smem_u32(smem);
    const int tid = threadIdx.x, warp = tid >> 5, lane = tid & 31;
    const int b = blockIdx.x, G = gridDim.x;
    const uint32_t bars = sb + SM_BAR;

    uint4 wm[8], wqr[8];
    uint32_t x2pk = 0, c2pk = 0, epoch_raw = 0;
    const int at = tid - (NCONS + 32);
    if (warp >= 5) {
        const int cc = at & 3, rg = at >> 2;
        if (b < N_MOD_CTA) {
#pragma unroll
            for (int i = 0; i < 8; i++) wm[i] = ldg_nc4(wmod + (size_t)(rg + 72 * i) * 3456 + b * 32 + cc * 8);
        }
        c2pk = *reinterpret_cast<const uint32_t*>(c_in + 2 * at);
        x2pk = *reinterpret_cast<const uint32_t*>(x_in + 2 * at);
        if (b < N_Q_CTA) {
#pragma unroll
            for (int i = 0; i < 8; i++) wqr[i] = ldg_nc4(wq + (size_t)(rg + 72 * i) * 4096 + b * 32 + cc * 8);
        }
    }
    if (warp != 4) epoch_raw = ld_poll1(&g_s.epoch[0]);
    if (tid == NCONS) {
        if (sb & 1023u) __trap();
        asm volatile("prefetch.tensormap [%0];" ::"l"(&tmK) : "memory");
        asm volatile("prefetch.tensormap [%0];" ::"l"(&tmV) : "memory");
#pragma unroll
        for (int s = 0; s < NSLOT; s++) { mbar_init(bars + B_FULL + s * 8, 1); mbar_init(bars + B_EMPTY + s * 8, 4); }
        mbar_init(bars + B_QRDY, NAUX / 32);
        mbar_init(bars + B_JOB, 1);
        mbar_init(bars + B_WO, 1);
        mbar_init(bars + B_GU, 1);
        mbar_init(bars + B_DOWN, 1);
        asm volatile("fence.mbarrier_init.release.cluster;" ::: "memory");
    }
    __syncthreads();

    if (warp == 4) {
        if (lane == 0) {
            TS(0);
            volatile int* s_tile = reinterpret_cast<volatile int*>(smem + SM_BAR + B_TILE);
            int t = b, tn = G + b;
            int s = 0;
            uint32_t ph = 1;
            bool first = true;
            while (true) {
                mbar_wait(bars + B_EMPTY + s * 8, ph);
                if (t >= NT) { s_tile[s] = -1; mbar_arrive(bars + B_FULL + s * 8); break; }
                s_tile[s] = t;
                mbar_expect_tx(bars + B_FULL + s * 8, SLOT_BYTES);
                tma3d(sb + SM_RING + s * SLOT_BYTES, &tmK, t * TILE, bars + B_FULL + s * 8);
                if (++s == NSLOT) { s = 0; ph ^= 1; }
                mbar_wait(bars + B_EMPTY + s * 8, ph);
                mbar_expect_tx(bars + B_FULL + s * 8, SLOT_BYTES);
                tma3d(sb + SM_RING + s * SLOT_BYTES, &tmV, t * TILE, bars + B_FULL + s * 8);
                if (++s == NSLOT) { s = 0; ph ^= 1; }
                t = tn;
                if (first) { first = false; tn = (int)atomicAdd(&g_s.ctr[0], 1u) + 2 * G; }
                else       { tn = (int)atomicAdd(&g_s.ctr[0], 1u) + 2 * G; }
            }
            TS(1);
        }
        return;
    }

    const uint32_t tag = (epoch_raw + 1u) & 3u;

    if (warp < 4) {
        const int g = lane >> 2, t4 = lane & 3;
        const volatile int* s_tile = reinterpret_cast<const volatile int*>(smem + SM_BAR + B_TILE);
        uint32_t offK[2], offV[2];
        {
            const int keyK = warp * 16 + (lane & 7) + ((lane >> 3) & 1) * 8, hiK = lane >> 4;
            const int keyV = warp * 16 + (lane & 7) + (lane >> 4) * 8, hiV = (lane >> 3) & 1;
#pragma unroll
            for (int h = 0; h < 2; h++) {
                offK[h] = keyK * 256 + h * 128 + ((hiK ^ ((keyK * 2 + h) & 7)) << 4);
                offV[h] = keyV * 256 + h * 128 + ((hiV ^ ((keyV * 2 + h) & 7)) << 4);
            }
        }
        float acc[8][4];
#pragma unroll
        for (int i = 0; i < 8; i++) { acc[i][0] = acc[i][1] = acc[i][2] = acc[i][3] = 0.f; }
        uint32_t mrun = M_INIT;
        float l0 = 0.f, l1 = 0.f;
        uint32_t qb[8][2];
        int cur = 0;
        int fpar = 0;
        const int jobhead = (b < N_JOB_CTA) ? (b >> 3) : -1;

        auto load_q = [&](int h) {
            const uint32_t* q32 = reinterpret_cast<const uint32_t*>(smem + SM_Q) + (2 * h + (g & 1)) * 64 + t4;
#pragma unroll
            for (int ks = 0; ks < 8; ks++) { qb[ks][0] = q32[ks * 8]; qb[ks][1] = q32[ks * 8 + 4]; }
        };
        auto flush = [&](int h) {
            float* fb = reinterpret_cast<float*>(smem + SM_FB) + (fpar * 4 + warp) * 256;
            float* fml = reinterpret_cast<float*>(smem + SM_FML) + fpar * 16;
            float la = l0, lb = l1;
#pragma unroll
            for (int o = 4; o < 32; o <<= 1) { la += __shfl_xor_sync(0xffffffffu, la, o); lb += __shfl_xor_sync(0xffffffffu, lb, o); }
#pragma unroll
            for (int i = 0; i < 8; i++) {
                if ((i >> 1) == t4) {
                    fb[16 * i + g] = acc[i][0];           fb[128 + 16 * i + g] = acc[i][1];
                    fb[16 * i + g + 8] = acc[i][2];       fb[128 + 16 * i + g + 8] = acc[i][3];
                }
            }
            if (lane == 0) {
                fml[warp * 4 + 0] = bf_lo(mrun); fml[warp * 4 + 1] = la;
                fml[warp * 4 + 2] = bf_hi(mrun); fml[warp * 4 + 3] = lb;
            }
            bar_sync(1, NCONS);
            if (tid == 0 && h == jobhead) mbar_arrive(bars + B_JOB);
            {
                const int hq = tid >> 6, d = (tid & 63) * 2;
                const float* f0 = reinterpret_cast<const float*>(smem + SM_FB) + fpar * 1024 + hq * 128 + d;
                float mw[4], M = -3.4e38f;
#pragma unroll
                for (int w = 0; w < 4; w++) { mw[w] = fml[w * 4 + hq * 2]; M = fmaxf(M, mw[w]); }
                float o0 = 0.f, o1 = 0.f, L = 0.f;
#pragma unroll
                for (int w = 0; w < 4; w++) {
                    const float sc = ex2((mw[w] - M) * LOG2E);
                    const float2 v = *reinterpret_cast<const float2*>(f0 + w * 256);
                    o0 = fmaf(sc, v.x, o0); o1 = fmaf(sc, v.y, o1);
                    L = fmaf(sc, fml[w * 4 + hq * 2 + 1], L);
                }
                st_pub2(&g_s.po[h][hq * 4 + (d >> 5)][b][d & 31], tagf(o0, tag), tagf(o1, tag));
                if ((tid & 63) == 0) st_pub2(&g_s.pml[h][hq][b][0], tagf(M, tag), tagf(L, tag));
            }
            fpar ^= 1;
#pragma unroll
            for (int i = 0; i < 8; i++) { acc[i][0] = acc[i][1] = acc[i][2] = acc[i][3] = 0.f; }
            mrun = M_INIT; l0 = 0.f; l1 = 0.f;
        };

        mbar_wait(bars + B_QRDY, 0);
        if (tid == 0) TS(2);
        load_q(0);
        int s = 0;
        uint32_t ph = 0;
        while (true) {
            mbar_wait(bars + B_FULL + s * 8, ph);
            const int t = s_tile[s];
            if (t < 0) break;
            const int h = t >> 10;
            if (h != cur) {
                for (; cur < h; cur++) flush(cur);
                load_q(h);
            }
            float sa[4] = {0.f, 0.f, 0.f, 0.f}, sc2[4] = {0.f, 0.f, 0.f, 0.f};
            {
                const uint32_t base = sb + SM_RING + s * SLOT_BYTES;
                uint32_t a[8][4];
#pragma unroll
                for (int ks = 0; ks < 8; ks++) ldsm4(a[ks], (base + offK[ks >> 2]) ^ ((ks & 3) << 5));
#pragma unroll
                for (int ks = 0; ks < 8; ks += 2) {
                    mma16816(sa, a[ks][0], a[ks][1], a[ks][2], a[ks][3], qb[ks][0], qb[ks][1]);
                    mma16816(sc2, a[ks + 1][0], a[ks + 1][1], a[ks + 1][2], a[ks + 1][3], qb[ks + 1][0], qb[ks + 1][1]);
                }
            }
            __syncwarp();
            if (lane == 0) mbar_arrive(bars + B_EMPTY + s * 8);
            if (++s == NSLOT) { s = 0; ph ^= 1; }
            uint32_t s01 = pack_bf16(sa[0] + sc2[0], sa[1] + sc2[1]);
            uint32_t s23 = pack_bf16(sa[2] + sc2[2], sa[3] + sc2[3]);
            s01 = pack_bf16(bf_lo(s01) * QK_SCALE, bf_hi(s01) * QK_SCALE);
            s23 = pack_bf16(bf_lo(s23) * QK_SCALE, bf_hi(s23) * QK_SCALE);
            uint32_t mx = max_bf16x2(s01, s23);
            mx = max_bf16x2(mx, __shfl_xor_sync(0xffffffffu, mx, 4));
            mx = max_bf16x2(mx, __shfl_xor_sync(0xffffffffu, mx, 8));
            mx = max_bf16x2(mx, __shfl_xor_sync(0xffffffffu, mx, 16));
            const uint32_t mnew = max_bf16x2(mrun, mx);
            if (mnew != mrun) {
                const float a0 = ex2((bf_lo(mrun) - bf_lo(mnew)) * LOG2E);
                const float a1 = ex2((bf_hi(mrun) - bf_hi(mnew)) * LOG2E);
                l0 *= a0; l1 *= a1;
#pragma unroll
                for (int i = 0; i < 8; i++) { acc[i][0] *= a0; acc[i][1] *= a1; acc[i][2] *= a0; acc[i][3] *= a1; }
                mrun = mnew;
            }
            const float m0 = bf_lo(mrun), m1 = bf_hi(mrun);
            const float p0 = ex2((bf_lo(s01) - m0) * LOG2E), p1 = ex2((bf_hi(s01) - m1) * LOG2E);
            const float p2 = ex2((bf_lo(s23) - m0) * LOG2E), p3 = ex2((bf_hi(s23) - m1) * LOG2E);
            l0 += p0 + p2; l1 += p1 + p3;
            const uint32_t pb0 = movmatrix_t(pack_bf16(p0, p1));
            const uint32_t pb1 = movmatrix_t(pack_bf16(p2, p3));
            mbar_wait(bars + B_FULL + s * 8, ph);
            {
                const uint32_t base = sb + SM_RING + s * SLOT_BYTES;
                uint32_t v[8][4];
#pragma unroll
                for (int i = 0; i < 8; i++) ldsm4t(v[i], (base + offV[i >> 2]) ^ ((i & 3) << 5));
#pragma unroll
                for (int i = 0; i < 8; i++) mma16816(acc[i], v[i][0], v[i][1], v[i][2], v[i][3], pb0, pb1);
            }
            __syncwarp();
            if (lane == 0) mbar_arrive(bars + B_EMPTY + s * 8);
            if (++s == NSLOT) { s = 0; ph ^= 1; }
        }
        if (tid == 0) TS(3);
        for (; cur < HKV; cur++) flush(cur);
        if (tid == 0) TS(4);
        return;
    }

    const int wa = at >> 5;
    const int g = lane >> 2, t4 = lane & 3;
    if (at == 0) {
        TS(5);
        if (b < N_JOB_CTA) {
            mbar_expect_tx(bars + B_WO, 32 * 1152);
            const __nv_bfloat16* src = wo + (size_t)b * 32 * D_MODEL;
            for (int r = 0; r < 32; r++) bulk1d(sb + SM_D + r * WPITCH, src + r * D_MODEL, 1152, bars + B_WO);
        }
        if (b < N_FFN_CTA) {
            mbar_expect_tx(bars + B_GU, 2 * SM_GSZ);
            for (int r = 0; r < 3; r++) {
                tma2d(sb + SM_G + r * 192 * 80, &tmG, b * FCOLS, r * 192, bars + B_GU);
                tma2d(sb + SM_G + SM_GSZ + r * 192 * 80, &tmU, b * FCOLS, r * 192, bars + B_GU);
            }
        }
    }
    float* pvec = reinterpret_cast<float*>(smem + SM_PRE_VEC);
    float* pred = reinterpret_cast<float*>(smem + SM_PRE_RED);
    float* pst = reinterpret_cast<float*>(smem + SM_PRE_ST);
    const float x0 = bf_lo(x2pk), x1 = bf_hi(x2pk);
    pvec[2 * at] = bfr(silu_f(bf_lo(c2pk)));
    pvec[2 * at + 1] = bfr(silu_f(bf_hi(c2pk)));
    float mean1, sd1;
    ln_stats(x0, x1, pst, at, mean1, sd1);
    const float ln0 = bfr(__fdiv_rn(bfr(x0 - mean1), sd1)), ln1 = bfr(__fdiv_rn(bfr(x1 - mean1), sd1));
    if (b < N_MOD_CTA) {
        gemv32_partial(wm, pvec, pred, at);
        bar_sync(2, NAUX);
        if (at < 32) {
            float sum = 0.f;
#pragma unroll
            for (int w = 0; w < 9; w++) sum += pred[w * 32 + at];
            st_pub1(&g_s.mod[b * 32 + at], __float_as_uint(bfr(sum)) | tag);
        }
    } else {
        bar_sync(2, NAUX);
    }
    if (at == 0) TS(6);
    {
        uint2 sa2, ca2;
        unsigned it = 0;
        do {
            sa2 = ld_poll2(&g_s.mod[2 * at]);
            ca2 = ld_poll2(&g_s.mod[D_MODEL + 2 * at]);
            if (++it > SPIN_MAX) __trap();
        } while (bad2(sa2, tag) | bad2(ca2, tag));
        const float h0 = bfr(bfr(ln0 * bfr(1.0f + untag_bf(ca2.x))) + untag_bf(sa2.x));
        const float h1 = bfr(bfr(ln1 * bfr(1.0f + untag_bf(ca2.y))) + untag_bf(sa2.y));
        pvec[2 * at] = h0; pvec[2 * at + 1] = h1;
    }
    bar_sync(2, NAUX);
    if (at == 0) TS(7);
    if (b < N_Q_CTA) {
        gemv32_partial(wqr, pvec, pred, at);
        bar_sync(2, NAUX);
        if (at < 32) {
            float sum = 0.f;
#pragma unroll
            for (int w = 0; w < 9; w++) sum += pred[w * 32 + at];
            st_pub1(&g_s.q[b * 32 + at], __float_as_uint(bfr(sum)) | tag);
        }
    }
    {
        uint4 v[4];
        unsigned it = 0;
        uint32_t bad;
        do {
            bad = 0;
#pragma unroll
            for (int r = 0; r < 4; r++) {
                const int idx = at + r * NAUX;
                if (idx < 1024) { v[r] = ld_poll4(&g_s.q[idx * 4]); bad |= bad4(v[r], tag); }
            }
            if (++it > SPIN_MAX) __trap();
        } while (bad);
        uint2* q_s = reinterpret_cast<uint2*>(smem + SM_Q);
#pragma unroll
        for (int r = 0; r < 4; r++) {
            const int idx = at + r * NAUX;
            if (idx < 1024) q_s[idx] = make_uint2((v[r].x >> 16) | (v[r].y & 0xffff0000u), (v[r].z >> 16) | (v[r].w & 0xffff0000u));
        }
        __syncwarp();
        if (lane == 0) mbar_arrive(bars + B_QRDY);
    }
    if (at == 0) TS(8);

    if (b < N_JOB_CTA) {
        const int h = b >> 3, sl = b & 7, hq = sl >> 2;
        float* jred = reinterpret_cast<float*>(smem + SM_JOB);
        float* jl = jred + 288;
        float* jm = jl + 16;
        uint32_t* o_s = reinterpret_cast<uint32_t*>(jm + 16);
        uint2 yprev = make_uint2(0u, 0u);
        mbar_wait(bars + B_JOB, 0);
        if (at == 0) TS(9);
        const int v = at & 7, bl = at >> 3;
        uint4 o4[4];
        uint2 ml[4];
        {
            unsigned it = 0;
            uint32_t bad;
            do {
                bad = 0;
#pragma unroll
                for (int r = 0; r < 4; r++) {
                    const int bb = bl + 36 * r;
                    if (bb < G) {
                        o4[r] = ld_poll4(&g_s.po[h][sl][bb][v * 4]);
                        ml[r] = ld_poll2(&g_s.pml[h][hq][bb][0]);
                        bad |= bad4(o4[r], tag) | bad2(ml[r], tag);
                    }
                }
                if (h > 0) { yprev = ld_poll2(&g_s.y[h - 1][sl][wa * 64 + 2 * lane]); bad |= bad2(yprev, tag); }
                if (++it > SPIN_MAX) __trap();
                if (bad && h != HKV - 1) __nanosleep(200);
            } while (bad);
        }
        if (at == 0) TS(10);
        float mloc = -3.4e38f;
#pragma unroll
        for (int r = 0; r < 4; r++) if (bl + 36 * r < G) mloc = fmaxf(mloc, untag_bf(ml[r].x));
        mloc = fmaxf(mloc, __shfl_xor_sync(0xffffffffu, mloc, 8));
        mloc = fmaxf(mloc, __shfl_xor_sync(0xffffffffu, mloc, 16));
        if (lane == 0) jm[wa] = mloc;
        bar_sync(2, NAUX);
        float M = jm[0];
#pragma unroll
        for (int w = 1; w < 9; w++) M = fmaxf(M, jm[w]);
        float a4[4] = {0.f, 0.f, 0.f, 0.f}, ls = 0.f;
#pragma unroll
        for (int r = 0; r < 4; r++) {
            if (bl + 36 * r < G) {
                const float w = ex2((untag_bf(ml[r].x) - M) * LOG2E);
                a4[0] = fmaf(w, __uint_as_float(o4[r].x), a4[0]); a4[1] = fmaf(w, __uint_as_float(o4[r].y), a4[1]);
                a4[2] = fmaf(w, __uint_as_float(o4[r].z), a4[2]); a4[3] = fmaf(w, __uint_as_float(o4[r].w), a4[3]);
                ls = fmaf(w, __uint_as_float(ml[r].y), ls);
            }
        }
#pragma unroll
        for (int o = 8; o < 32; o <<= 1) {
#pragma unroll
            for (int j = 0; j < 4; j++) a4[j] += __shfl_xor_sync(0xffffffffu, a4[j], o);
            ls += __shfl_xor_sync(0xffffffffu, ls, o);
        }
        if (lane < 8) *reinterpret_cast<float4*>(&jred[wa * 32 + lane * 4]) = make_float4(a4[0], a4[1], a4[2], a4[3]);
        if (lane == 0) jl[wa] = ls;
        bar_sync(2, NAUX);
        if (at < 16) {
            float s0 = 0.f, s1 = 0.f, L = 0.f;
#pragma unroll
            for (int w = 0; w < 9; w++) { s0 += jred[w * 32 + 2 * at]; s1 += jred[w * 32 + 2 * at + 1]; L += jl[w]; }
            o_s[at] = pack_bf16(__fdividef(s0, L), __fdividef(s1, L));
        }
        mbar_wait(bars + B_WO, 0);
        bar_sync(2, NAUX);
        {
            const uint32_t a00 = o_s[t4], a02 = o_s[4 + t4], a10 = o_s[8 + t4], a12 = o_s[12 + t4];
            float y[8][4];
            const uint32_t wbase = sb + SM_D + lane * WPITCH + wa * 128;
#pragma unroll
            for (int j = 0; j < 8; j++) {
                uint32_t bb[4];
                ldsm4t(bb, wbase + j * 16);
                y[j][0] = y[j][1] = y[j][2] = y[j][3] = 0.f;
                mma16816(y[j], a00, 0u, a02, 0u, bb[0], bb[1]);
                mma16816(y[j], a10, 0u, a12, 0u, bb[2], bb[3]);
            }
            float r0 = 0.f, r1 = 0.f;
#pragma unroll
            for (int j = 0; j < 8; j++) if (g == j) { r0 = y[j][0]; r1 = y[j][1]; }
            if (h > 0) { r0 += __uint_as_float(yprev.x); r1 += __uint_as_float(yprev.y); }
            st_pub2(&g_s.y[h][sl][wa * 64 + 2 * lane], tagf(r0, tag), tagf(r1, tag));
        }
        if (at == 0) TS(11);
        if (b < N_FFN_CTA) {
            asm volatile("fence.proxy.async.shared::cta;" ::: "memory");
            bar_sync(2, NAUX);
            if (at == 0) {
                mbar_expect_tx(bars + B_DOWN, FCOLS * 1152);
                for (int r = 0; r < FCOLS; r++) {
                    const int row = min(b * FCOLS + r, FF - 1);
                    bulk1d(sb + SM_D + r * WPITCH, wdown + (size_t)row * D_MODEL, 1152, bars + B_DOWN);
                }
            }
        }
    }
    if (b >= N_FFN_CTA) return;

    uint2 ga2, sb2, cb2;
    {
        unsigned it = 0;
        do {
            ga2 = ld_poll2(&g_s.mod[2 * D_MODEL + 2 * at]);
            sb2 = ld_poll2(&g_s.mod[3 * D_MODEL + 2 * at]);
            cb2 = ld_poll2(&g_s.mod[4 * D_MODEL + 2 * at]);
            if (++it > SPIN_MAX) __trap();
        } while (bad2(ga2, tag) | bad2(sb2, tag) | bad2(cb2, tag));
    }
    uint32_t gbv = 0;
    if (b < N_FIN_CTA && at < 8) {
        unsigned it = 0;
        do { gbv = ld_poll1(&g_s.mod[5 * D_MODEL + b * 8 + at]); if (++it > SPIN_MAX) __trap(); } while ((gbv ^ tag) & 3u);
    }
    {
        unsigned it = 0;
        while ((ld_poll1(&g_s.pml[HKV - 1][0][b][0]) ^ tag) & 3u) { __nanosleep(500); if (++it > SPIN_MAX) __trap(); }
    }
    if (at == 0) TS(12);
    float* ys = reinterpret_cast<float*>(smem + SM_T_YS);
    float* x2s = reinterpret_cast<float*>(smem + SM_T_X2);
    uint32_t* h2s = reinterpret_cast<uint32_t*>(smem + SM_T_H2);
    float* tred = reinterpret_cast<float*>(smem + SM_T_RED);
    float* tst = reinterpret_cast<float*>(smem + SM_T_ST);
    uint32_t* acts = reinterpret_cast<uint32_t*>(smem + SM_T_ACT);
    float* tfin = reinterpret_cast<float*>(smem + SM_T_FIN);
    {
        const int cq = (at >= 144) ? at - 144 : at, sg = (at >= 144) ? 1 : 0;
        uint4 v[4];
        unsigned it = 0;
        uint32_t bad;
        do {
            bad = 0;
#pragma unroll
            for (int r = 0; r < 4; r++) { v[r] = ld_poll4(&g_s.y[HKV - 1][sg * 4 + r][cq * 4]); bad |= bad4(v[r], tag); }
            if (++it > SPIN_MAX) __trap();
        } while (bad);
        float4 sum;
        sum.x = (__uint_as_float(v[0].x) + __uint_as_float(v[1].x)) + (__uint_as_float(v[2].x) + __uint_as_float(v[3].x));
        sum.y = (__uint_as_float(v[0].y) + __uint_as_float(v[1].y)) + (__uint_as_float(v[2].y) + __uint_as_float(v[3].y));
        sum.z = (__uint_as_float(v[0].z) + __uint_as_float(v[1].z)) + (__uint_as_float(v[2].z) + __uint_as_float(v[3].z));
        sum.w = (__uint_as_float(v[0].w) + __uint_as_float(v[1].w)) + (__uint_as_float(v[2].w) + __uint_as_float(v[3].w));
        *reinterpret_cast<float4*>(&ys[sg * D_MODEL + cq * 4]) = sum;
    }
    if (at == 0) TS(13);
    bar_sync(2, NAUX);
    {
        const float a0 = bfr(ys[2 * at] + ys[D_MODEL + 2 * at]), a1 = bfr(ys[2 * at + 1] + ys[D_MODEL + 2 * at + 1]);
        const float y0 = bfr(x0 + bfr(untag_bf(ga2.x) * a0)), y1 = bfr(x1 + bfr(untag_bf(ga2.y) * a1));
        x2s[2 * at] = y0; x2s[2 * at + 1] = y1;
        float mean2, sd2;
        ln_stats(y0, y1, tst, at, mean2, sd2);
        const float n0 = bfr(__fdiv_rn(bfr(y0 - mean2), sd2)), n1 = bfr(__fdiv_rn(bfr(y1 - mean2), sd2));
        const float h0 = bfr(bfr(n0 * bfr(1.0f + untag_bf(cb2.x))) + untag_bf(sb2.x));
        const float h1 = bfr(bfr(n1 * bfr(1.0f + untag_bf(cb2.y))) + untag_bf(sb2.y));
        h2s[at] = pack_bf16(h0, h1);
    }
    mbar_wait(bars + B_GU, 0);
    bar_sync(2, NAUX);
    if (at == 0) TS(14);
    {
        uint32_t alo[4], ahi[4];
#pragma unroll
        for (int ks = 0; ks < 4; ks++) { alo[ks] = h2s[wa * 32 + ks * 8 + t4]; ahi[ks] = h2s[wa * 32 + ks * 8 + 4 + t4]; }
#pragma unroll
        for (int m = 0; m < 2; m++) {
            const uint32_t wbase = sb + SM_G + m * SM_GSZ + (wa * 64 + lane) * 80;
#pragma unroll
            for (int j = 0; j < 5; j++) {
                uint32_t b0[4], b1[4];
                ldsm4t(b0, wbase + j * 16);
                ldsm4t(b1, wbase + 32 * 80 + j * 16);
                float y[4] = {0.f, 0.f, 0.f, 0.f}, z[4] = {0.f, 0.f, 0.f, 0.f};
                mma16816(y, alo[0], 0u, ahi[0], 0u, b0[0], b0[1]);
                mma16816(z, alo[2], 0u, ahi[2], 0u, b1[0], b1[1]);
                mma16816(y, alo[1], 0u, ahi[1], 0u, b0[2], b0[3]);
                mma16816(z, alo[3], 0u, ahi[3], 0u, b1[2], b1[3]);
                if (g == 0) *reinterpret_cast<float2*>(&tred[wa * 80 + m * 40 + j * 8 + 2 * t4]) = make_float2(y[0] + z[0], y[1] + z[1]);
            }
        }
    }
    bar_sync(2, NAUX);
    if (at < 20) {
        float g0 = 0.f, g1 = 0.f, u0 = 0.f, u1 = 0.f;
#pragma unroll
        for (int w = 0; w < 9; w++) {
            const float2 gg = *reinterpret_cast<const float2*>(&tred[w * 80 + 2 * at]);
            const float2 uu = *reinterpret_cast<const float2*>(&tred[w * 80 + 40 + 2 * at]);
            g0 += gg.x; g1 += gg.y; u0 += uu.x; u1 += uu.y;
        }
        const float a0 = bfr(silu_f(bfr(g0))) * bfr(u0), a1 = bfr(silu_f(bfr(g1))) * bfr(u1);
        acts[at] = pack_bf16(a0, a1);
    }
    mbar_wait(bars + B_DOWN, 0);
    bar_sync(2, NAUX);
    if (at == 0) TS(15);
    {
        const uint32_t a00 = acts[t4], a02 = acts[4 + t4], a10 = acts[8 + t4], a12 = acts[12 + t4], a20 = acts[16 + t4];
        float y[8][4];
        const uint32_t wbase = sb + SM_D + lane * WPITCH + wa * 128;
        const uint32_t wbase2 = sb + SM_D + (32 + (lane & 7)) * WPITCH + wa * 128;
#pragma unroll
        for (int j = 0; j < 8; j++) {
            uint32_t bb[4], b2;
            ldsm4t(bb, wbase + j * 16);
            ldsm1t(b2, wbase2 + j * 16);
            y[j][0] = y[j][1] = y[j][2] = y[j][3] = 0.f;
            mma16816(y[j], a00, 0u, a02, 0u, bb[0], bb[1]);
            mma16816(y[j], a10, 0u, a12, 0u, bb[2], bb[3]);
            mma1688(y[j], a20, 0u, b2);
        }
        float r0 = 0.f, r1 = 0.f;
#pragma unroll
        for (int j = 0; j < 8; j++) if (g == j) { r0 = y[j][0]; r1 = y[j][1]; }
        st_pub2(&g_s.y2[b][wa * 64 + 2 * lane], tagf(r0, tag), tagf(r1, tag));
    }
    if (at == 0) TS(16);
    if (b >= N_FIN_CTA) return;
    {
        float a4[4] = {0.f, 0.f, 0.f, 0.f};
        if (at < 2 * N_FFN_CTA) {
            uint4 v;
            unsigned it = 0;
            do { v = ld_poll4(&g_s.y2[at >> 1][b * 8 + (at & 1) * 4]); if (++it > SPIN_MAX) __trap(); } while (bad4(v, tag));
            a4[0] = __uint_as_float(v.x); a4[1] = __uint_as_float(v.y); a4[2] = __uint_as_float(v.z); a4[3] = __uint_as_float(v.w);
        }
        __syncwarp();
#pragma unroll
        for (int o = 2; o < 32; o <<= 1) {
#pragma unroll
            for (int j = 0; j < 4; j++) a4[j] += __shfl_xor_sync(0xffffffffu, a4[j], o);
        }
        if (lane < 2) *reinterpret_cast<float4*>(&tfin[wa * 8 + lane * 4]) = make_float4(a4[0], a4[1], a4[2], a4[3]);
        bar_sync(2, NAUX);
        if (at < 8) {
            float sum = 0.f;
#pragma unroll
            for (int w = 0; w < 8; w++) sum += tfin[w * 8 + at];
            const float d = bfr(sum);
            const float r = x2s[b * 8 + at] + bfr(untag_bf(gbv) * d);
            out[b * 8 + at] = __float2bfloat16_rn(r);
        }
        if (b == 0 && at == 0) {
            g_s.ctr[0] = 0u;
            g_s.epoch[0] = epoch_raw + 1u;
            TS(17);
        }
    }
}

typedef CUresult (*EncodeFn)(CUtensorMap*, CUtensorMapDataType, cuuint32_t, void*, const cuuint64_t*, const cuuint64_t*,
                             const cuuint32_t*, const cuuint32_t*, CUtensorMapInterleave, CUtensorMapSwizzle,
                             CUtensorMapL2promotion, CUtensorMapFloatOOBfill);

}

extern "C" void kernel_launch(void* const* d_in, const int* in_sizes, int n_in, void* d_out, int out_size) {
    (void)in_sizes; (void)n_in; (void)out_size;
    static EncodeFn enc = nullptr;
    static int nsm = 0;
    if (!enc) {
        void* fn = nullptr;
        cudaDriverEntryPointQueryResult qr;
        cudaGetDriverEntryPoint("cuTensorMapEncodeTiled", &fn, cudaEnableDefault, &qr);
        enc = (EncodeFn)fn;
        int dev = 0;
        cudaGetDevice(&dev);
        cudaDeviceGetAttribute(&nsm, cudaDevAttrMultiProcessorCount, dev);
        cudaFuncSetAttribute(fused_kernel, cudaFuncAttributeMaxDynamicSharedMemorySize, SM_TOTAL);
    }
    if (!enc) return;
    const __nv_bfloat16* x = (const __nv_bfloat16*)d_in[0];
    void* kc = d_in[1];
    void* vc = d_in[2];
    const __nv_bfloat16* wq = (const __nv_bfloat16*)d_in[3];
    const __nv_bfloat16* wo = (const __nv_bfloat16*)d_in[4];
    void* wg = d_in[6];
    void* wu = d_in[7];
    const __nv_bfloat16* wd = (const __nv_bfloat16*)d_in[8];
    const __nv_bfloat16* c = (const __nv_bfloat16*)d_in[9];
    const __nv_bfloat16* wmod = (const __nv_bfloat16*)d_in[10];

    CUtensorMap tmK, tmV, tmG, tmU;
    {
        cuuint64_t gd[3] = {64, 2, (cuuint64_t)HKV * SK};
        cuuint64_t gs[2] = {128, 256};
        cuuint32_t bx[3] = {64, 2, TILE};
        cuuint32_t es[3] = {1, 1, 1};
        enc(&tmK, CU_TENSOR_MAP_DATA_TYPE_BFLOAT16, 3, kc, gd, gs, bx, es, CU_TENSOR_MAP_INTERLEAVE_NONE,
            CU_TENSOR_MAP_SWIZZLE_128B, CU_TENSOR_MAP_L2_PROMOTION_NONE, CU_TENSOR_MAP_FLOAT_OOB_FILL_NONE);
        enc(&tmV, CU_TENSOR_MAP_DATA_TYPE_BFLOAT16, 3, vc, gd, gs, bx, es, CU_TENSOR_MAP_INTERLEAVE_NONE,
            CU_TENSOR_MAP_SWIZZLE_128B, CU_TENSOR_MAP_L2_PROMOTION_NONE, CU_TENSOR_MAP_FLOAT_OOB_FILL_NONE);
    }
    {
        cuuint64_t gd[2] = {FF, D_MODEL};
        cuuint64_t gs[1] = {FF * 2};
        cuuint32_t bx[2] = {FCOLS, 192};
        cuuint32_t es[2] = {1, 1};
        enc(&tmG, CU_TENSOR_MAP_DATA_TYPE_BFLOAT16, 2, wg, gd, gs, bx, es, CU_TENSOR_MAP_INTERLEAVE_NONE,
            CU_TENSOR_MAP_SWIZZLE_NONE, CU_TENSOR_MAP_L2_PROMOTION_L2_256B, CU_TENSOR_MAP_FLOAT_OOB_FILL_NONE);
        enc(&tmU, CU_TENSOR_MAP_DATA_TYPE_BFLOAT16, 2, wu, gd, gs, bx, es, CU_TENSOR_MAP_INTERLEAVE_NONE,
            CU_TENSOR_MAP_SWIZZLE_NONE, CU_TENSOR_MAP_L2_PROMOTION_L2_256B, CU_TENSOR_MAP_FLOAT_OOB_FILL_NONE);
    }
    int grid = nsm < MAXG ? nsm : MAXG;
    if (grid < N_JOB_CTA) return;
    fused_kernel<<<grid, NTHREADS, SM_TOTAL, cudaStreamPerThread>>>(tmK, tmV, tmG, tmU, x, wq, wo, wd, c, wmod,
                                                                   (__nv_bfloat16*)d_out);
}
```

```cpp
#include <cuda_runtime.h>
#include <cuda_bf16.h>
#include <cuda.h>
#include <stdint.h>

namespace {

constexpr int D_MODEL = 576;
constexpr int HKV = 16;
constexpr int SK = 65536;
constexpr int FF = 4608;
constexpr int TILE = 64;
constexpr int TPH = SK / TILE;
constexpr int NT = HKV * TPH;
#define EXP_NSLOT 3
constexpr int NSLOT = EXP_NSLOT;
constexpr int RING_SLOTS = 4;
constexpr int SLOT_BYTES = TILE * 256;
constexpr int MAXG = 144;
constexpr int N_MOD_CTA = 108;
constexpr int N_Q_CTA = 128;
constexpr int N_JOB_CTA = 128;
constexpr int N_FFN_CTA = 116;
constexpr int N_FIN_CTA = 72;
constexpr int FCOLS = 40;

#define JOB_DELAY_CLK 8000
#define START_PACE 1
#define DRY_CONS 0
#define DRY_AUX 0
#define PF_ITEMS 0
#define PF_WHEN 0
#define LATE_GATE 2
#define LATE_WIN 4
#define U_PROMO CU_TENSOR_MAP_L2_PROMOTION_L2_256B
#define D_PROMO CU_TENSOR_MAP_L2_PROMOTION_NONE
#define LATE_MODE 0
#define EXP_NOLATE 0
#define DE_GROUPS 0

constexpr int NCONS = 128;
constexpr int NAUX = 288;
constexpr int NTHREADS = NCONS + 32 + NAUX;

constexpr int SM_RING = 0;
constexpr int SM_G = SM_RING + RING_SLOTS * SLOT_BYTES;
constexpr int SM_GSZ = D_MODEL * FCOLS * 2;
constexpr int SM_U = SM_G + SM_GSZ;
constexpr int SM_D = SM_U + SM_GSZ;
constexpr int SM_DGRP = FCOLS * 128;
constexpr int SM_OGRP = 32 * 128;
constexpr int SM_Q = SM_D + 9 * SM_DGRP;
constexpr int SM_FB = SM_Q + 8192;
constexpr int SM_FML = SM_FB + 8192;
constexpr int SM_X = SM_FML + 128;
constexpr int SM_T = SM_X + 4096;
constexpr int SM_BAR = SM_T + 6144;
constexpr int SM_TOTAL = SM_BAR + 256;
static_assert(SM_U % 1024 == 0 && SM_D % 1024 == 0, "swizzled regions must be 1024-aligned");
static_assert(SM_TOTAL <= 232448, "smem");
constexpr int X_ST1 = SM_X;
constexpr int X_ST2 = SM_X + 128;
constexpr int X_RED0 = SM_X + 256;
constexpr int X_RED1 = X_RED0 + 1152;
constexpr int X_JML = X_RED1 + 1152;
constexpr int X_ACT = X_JML + 128;
constexpr int X_FIN = X_ACT + 128;
constexpr int T_GU = SM_T;
constexpr int T_X2 = SM_T + 3072;
static_assert(X_FIN + 384 <= SM_T, "aux scratch");

constexpr int B_FULL = 0;
constexpr int B_EMPTY = 32;
constexpr int B_QRDY = 64;
constexpr int B_JOB = 72;
constexpr int B_WO = 80;
constexpr int B_G = 88;
constexpr int B_U = 96;
constexpr int B_DOWN = 104;
constexpr int B_WM = 120;
constexpr int B_WQ = 128;
constexpr int B_FREE = 136;
constexpr int B_PACE = 144;
constexpr int B_TILE = 192;

constexpr unsigned SPIN_MAX = 1u << 21;

constexpr int PROW = 40;
struct Scratch {
    uint32_t mod[3456];
    uint32_t q[4096];
    uint32_t po[HKV][8][MAXG][PROW];
    uint32_t y[HKV][8][D_MODEL];
    uint32_t y2[N_FFN_CTA][D_MODEL];
    uint32_t ctr[32];
    uint32_t epoch[32];
};
__device__ __align__(128) Scratch g_s;

#define TS(i) do { } while (0)
#define TC(i) do { } while (0)

__device__ __forceinline__ uint32_t smem_u32(const void* p) { return (uint32_t)__cvta_generic_to_shared(p); }
__device__ __forceinline__ void mbar_init(uint32_t bar, uint32_t cnt) {
    asm volatile("mbarrier.init.shared::cta.b64 [%0], %1;" ::"r"(bar), "r"(cnt) : "memory");
}
__device__ __forceinline__ void mbar_expect_tx(uint32_t bar, uint32_t bytes) {
    asm volatile("mbarrier.arrive.expect_tx.shared::cta.b64 _, [%0], %1;" ::"r"(bar), "r"(bytes) : "memory");
}
__device__ __forceinline__ void mbar_arrive(uint32_t bar) {
    asm volatile("mbarrier.arrive.shared::cta.b64 _, [%0];" ::"r"(bar) : "memory");
}
__device__ __forceinline__ bool mbar_try(uint32_t bar, uint32_t parity) {
    uint32_t ok;
    asm volatile("{\n.reg .pred p;\nmbarrier.try_wait.parity.shared::cta.b64 p, [%1], %2;\nselp.u32 %0, 1, 0, p;\n}"
                 : "=r"(ok) : "r"(bar), "r"(parity) : "memory");
    return ok != 0;
}
__device__ __forceinline__ bool mbar_test(uint32_t bar, uint32_t parity) {
    uint32_t ok;
    asm volatile("{\n.reg .pred p;\nmbarrier.test_wait.parity.shared::cta.b64 p, [%1], %2;\nselp.u32 %0, 1, 0, p;\n}"
                 : "=r"(ok) : "r"(bar), "r"(parity) : "memory");
    return ok != 0;
}
__device__ __forceinline__ void mbar_wait(uint32_t bar, uint32_t parity) {
    if (mbar_try(bar, parity)) return;
    const long long t0 = clock64();
    while (!mbar_try(bar, parity)) {
        if (clock64() - t0 > (1ll << 31)) __trap();
    }
}
__device__ __forceinline__ void mbar_wait_long(uint32_t bar, uint32_t parity) {
    const long long t0 = clock64();
    while (true) {
        uint32_t ok;
        asm volatile("{\n.reg .pred p;\nmbarrier.try_wait.parity.shared::cta.b64 p, [%1], %2, %3;\nselp.u32 %0, 1, 0, p;\n}"
                     : "=r"(ok) : "r"(bar), "r"(parity), "r"(200000u) : "memory");
        if (ok) return;
        if (clock64() - t0 > (1ll << 31)) __trap();
    }
}
__device__ __forceinline__ void bar_sync(int id, int n) { asm volatile("bar.sync %0, %1;" ::"r"(id), "r"(n) : "memory"); }
__device__ __forceinline__ void bar_arrive(int id, int n) { asm volatile("bar.arrive %0, %1;" ::"r"(id), "r"(n) : "memory"); }
__device__ __forceinline__ void fence_async_smem() { asm volatile("fence.proxy.async.shared::cta;" ::: "memory"); }

__device__ __forceinline__ uint64_t policy_evict_first() {
    uint64_t p;
    asm volatile("createpolicy.fractional.L2::evict_first.b64 %0, 1.0;" : "=l"(p));
    return p;
}
__device__ __forceinline__ void tma3d(uint32_t dst, const CUtensorMap* m, int c2, uint32_t bar, uint64_t pol) {
    asm volatile("cp.async.bulk.tensor.3d.shared::cluster.global.mbarrier::complete_tx::bytes.L2::cache_hint [%0], [%1, {%3, %3, %4}], [%2], %5;"
                 ::"r"(dst), "l"(m), "r"(bar), "r"(0), "r"(c2), "l"(pol) : "memory");
}
__device__ __forceinline__ void tma3d_prefetch(const CUtensorMap* m, int c2, uint64_t pol) {
    asm volatile("cp.async.bulk.prefetch.tensor.3d.L2.global.tile.L2::cache_hint [%0, {%1, %1, %2}], %3;"
                 ::"l"(m), "r"(0), "r"(c2), "l"(pol) : "memory");
}
__device__ __forceinline__ void tma2d(uint32_t dst, const CUtensorMap* m, int c0, int c1, uint32_t bar) {
    asm volatile("cp.async.bulk.tensor.2d.shared::cluster.global.mbarrier::complete_tx::bytes [%0], [%1, {%3, %4}], [%2];"
                 ::"r"(dst), "l"(m), "r"(bar), "r"(c0), "r"(c1) : "memory");
}
__device__ __forceinline__ void ldsm4(uint32_t (&r)[4], uint32_t addr) {
    asm volatile("ldmatrix.sync.aligned.m8n8.x4.shared.b16 {%0,%1,%2,%3}, [%4];"
                 : "=r"(r[0]), "=r"(r[1]), "=r"(r[2]), "=r"(r[3]) : "r"(addr) : "memory");
}
__device__ __forceinline__ void ldsm4t(uint32_t (&r)[4], uint32_t addr) {
    asm volatile("ldmatrix.sync.aligned.m8n8.x4.trans.shared.b16 {%0,%1,%2,%3}, [%4];"
                 : "=r"(r[0]), "=r"(r[1]), "=r"(r[2]), "=r"(r[3]) : "r"(addr) : "memory");
}
__device__ __forceinline__ void ldsm2t(uint32_t& r0, uint32_t& r1, uint32_t addr) {
    asm volatile("ldmatrix.sync.aligned.m8n8.x2.trans.shared.b16 {%0,%1}, [%2];" : "=r"(r0), "=r"(r1) : "r"(addr) : "memory");
}
__device__ __forceinline__ void mma16816(float (&c)[4], uint32_t a0, uint32_t a1, uint32_t a2, uint32_t a3, uint32_t b0, uint32_t b1) {
    asm volatile("mma.sync.aligned.m16n8k16.row.col.f32.bf16.bf16.f32 {%0,%1,%2,%3}, {%4,%5,%6,%7}, {%8,%9}, {%0,%1,%2,%3};"
                 : "+f"(c[0]), "+f"(c[1]), "+f"(c[2]), "+f"(c[3])
                 : "r"(a0), "r"(a1), "r"(a2), "r"(a3), "r"(b0), "r"(b1));
}
__device__ __forceinline__ void mma1688(float (&c)[4], uint32_t a0, uint32_t a1, uint32_t b0) {
    asm volatile("mma.sync.aligned.m16n8k8.row.col.f32.bf16.bf16.f32 {%0,%1,%2,%3}, {%4,%5}, {%6}, {%0,%1,%2,%3};"
                 : "+f"(c[0]), "+f"(c[1]), "+f"(c[2]), "+f"(c[3])
                 : "r"(a0), "r"(a1), "r"(b0));
}
__device__ __forceinline__ uint32_t movmatrix_t(uint32_t a) {
    uint32_t d;
    asm volatile("movmatrix.sync.aligned.m8n8.trans.b16 %0, %1;" : "=r"(d) : "r"(a));
    return d;
}
__device__ __forceinline__ uint32_t pack_bf16(float lo, float hi) {
    uint32_t d;
    asm("cvt.rn.bf16x2.f32 %0, %1, %2;" : "=r"(d) : "f"(hi), "f"(lo));
    return d;
}
__device__ __forceinline__ float bf_lo(uint32_t v) { return __uint_as_float(v << 16); }
__device__ __forceinline__ float bf_hi(uint32_t v) { return __uint_as_float(v & 0xffff0000u); }
__device__ __forceinline__ float bfr(float x) { return bf_lo(pack_bf16(x, 0.f)); }
__device__ __forceinline__ uint32_t max_bf16x2(uint32_t a, uint32_t b) {
    uint32_t d;
    asm("max.bf16x2 %0, %1, %2;" : "=r"(d) : "r"(a), "r"(b));
    return d;
}
__device__ __forceinline__ float ex2(float x) {
    float y;
    asm("ex2.approx.ftz.f32 %0, %1;" : "=f"(y) : "f"(x));
    return y;
}
__device__ __forceinline__ float silu_f(float x) { return __fdividef(x, 1.0f + __expf(-x)); }

__device__ __forceinline__ uint4 ld_poll4(const uint32_t* p) {
    uint4 v;
    asm volatile("ld.relaxed.gpu.global.v4.u32 {%0,%1,%2,%3}, [%4];" : "=r"(v.x), "=r"(v.y), "=r"(v.z), "=r"(v.w) : "l"(p) : "memory");
    return v;
}
__device__ __forceinline__ uint2 ld_poll2(const uint32_t* p) {
    uint2 v;
    asm volatile("ld.relaxed.gpu.global.v2.u32 {%0,%1}, [%2];" : "=r"(v.x), "=r"(v.y) : "l"(p) : "memory");
    return v;
}
__device__ __forceinline__ uint32_t ld_poll1(const uint32_t* p) {
    uint32_t v;
    asm volatile("ld.relaxed.gpu.global.u32 %0, [%1];" : "=r"(v) : "l"(p) : "memory");
    return v;
}
__device__ __forceinline__ void st_pub1(uint32_t* p, uint32_t a) {
    asm volatile("st.relaxed.gpu.global.u32 [%0], %1;" ::"l"(p), "r"(a) : "memory");
}
__device__ __forceinline__ void st_pub2(uint32_t* p, uint32_t a, uint32_t b) {
    asm volatile("st.relaxed.gpu.global.v2.u32 [%0], {%1,%2};" ::"l"(p), "r"(a), "r"(b) : "memory");
}
__device__ __forceinline__ void st_pub4(uint32_t* p, uint32_t a) {
    asm volatile("st.relaxed.gpu.global.v4.u32 [%0], {%1,%1,%1,%1};" ::"l"(p), "r"(a) : "memory");
}
__device__ __forceinline__ uint32_t tagf(float v, uint32_t tag) { return (__float_as_uint(v) & ~3u) | tag; }
__device__ __forceinline__ uint32_t bad4(const uint4& v, uint32_t tag) { return ((v.x ^ tag) | (v.y ^ tag) | (v.z ^ tag) | (v.w ^ tag)) & 3u; }
__device__ __forceinline__ uint32_t bad2(const uint2& v, uint32_t tag) { return ((v.x ^ tag) | (v.y ^ tag)) & 3u; }
__device__ __forceinline__ float untag_bf(uint32_t v) { return __uint_as_float(v & 0xffff0000u); }

constexpr float LOG2E = 1.4426950408889634f;
constexpr float QK_SCALE = 0.08838834764831845f;
constexpr uint32_t M_INIT = 0xFF7FFF7Fu;

__device__ __forceinline__ void ln_stats(float x0, float x1, float* st, int at, float& mean_r, float& rsd) {
    const float piv = __shfl_sync(0xffffffffu, x0, 0);
    const float d0 = x0 - piv, d1 = x1 - piv;
    float s1 = d0 + d1, s2 = fmaf(d0, d0, d1 * d1);
#pragma unroll
    for (int o = 1; o < 32; o <<= 1) {
        s1 += __shfl_xor_sync(0xffffffffu, s1, o);
        s2 += __shfl_xor_sync(0xffffffffu, s2, o);
    }
    if ((at & 31) == 0)
        *reinterpret_cast<float2*>(&st[(at >> 5) * 2]) = make_float2(fmaf(s1, 1.0f / 64.0f, piv), fmaf(s1 * s1, -1.0f / 64.0f, s2));
    bar_sync(2, NAUX);
    float2 sw[9];
#pragma unroll
    for (int w = 0; w < 9; w++) sw[w] = *reinterpret_cast<const float2*>(&st[2 * w]);
    const float ms = (((sw[0].x + sw[1].x) + (sw[2].x + sw[3].x)) + ((sw[4].x + sw[5].x) + (sw[6].x + sw[7].x))) + sw[8].x;
    const float m2s = (((sw[0].y + sw[1].y) + (sw[2].y + sw[3].y)) + ((sw[4].y + sw[5].y) + (sw[6].y + sw[7].y))) + sw[8].y;
    const float mu = ms * (1.0f / 9.0f);
    float e[9];
#pragma unroll
    for (int w = 0; w < 9; w++) e[w] = sw[w].x - mu;
    const float dd = ((fmaf(e[0], e[0], e[1] * e[1]) + fmaf(e[2], e[2], e[3] * e[3])) +
                      (fmaf(e[4], e[4], e[5] * e[5]) + fmaf(e[6], e[6], e[7] * e[7]))) + e[8] * e[8];
    const float var = fmaxf(fmaf(64.f, dd, m2s), 0.f) * (1.0f / 576.0f);
    mean_r = bfr(mu);
    float sd;
    asm("sqrt.approx.f32 %0, %1;" : "=f"(sd) : "f"(bfr(bfr(var) + 1e-5f)));
    sd = bfr(sd);
    asm("rcp.approx.f32 %0, %1;" : "=f"(rsd) : "f"(sd));
}
__device__ __forceinline__ uint32_t modulate2(float x0, float x1, float mean_r, float rsd, uint2 scale, uint2 shift) {
    const uint32_t dpk = pack_bf16(x0 - mean_r, x1 - mean_r);
    const uint32_t npk = pack_bf16(bf_lo(dpk) * rsd, bf_hi(dpk) * rsd);
    const uint32_t cpk = pack_bf16(1.0f + untag_bf(scale.x), 1.0f + untag_bf(scale.y));
    const uint32_t mpk = pack_bf16(bf_lo(npk) * bf_lo(cpk), bf_hi(npk) * bf_hi(cpk));
    return pack_bf16(bf_lo(mpk) + untag_bf(shift.x), bf_hi(mpk) + untag_bf(shift.y));
}
__device__ __forceinline__ float sum9(const float* p, int stride) {
    float v[9];
#pragma unroll
    for (int w = 0; w < 9; w++) v[w] = p[w * stride];
    return (((v[0] + v[1]) + (v[2] + v[3])) + ((v[4] + v[5]) + (v[6] + v[7]))) + v[8];
}
__device__ __forceinline__ int opaque(int v) { asm volatile("" : "+r"(v)); return v; }

__device__ __forceinline__ void load_frag32(uint32_t (&a)[8][4], uint32_t base, int wa, int lane) {
    const int mi = lane >> 3;
#pragma unroll
    for (int ks = 0; ks < 4; ks++) {
        const int r = wa * 64 + ks * 16 + (lane & 7) + (mi >> 1) * 8;
#pragma unroll
        for (int j = 0; j < 2; j++) {
            const int c = 2 * j + (mi & 1);
            ldsm4t(a[j * 4 + ks], base + r * 64 + ((c ^ ((r >> 1) & 3)) << 4));
        }
    }
}
__device__ __forceinline__ void gemv32(const uint32_t (&a)[8][4], uint32_t pk, float* red, int wa, int lane) {
    const int g = lane >> 2, t4 = lane & 3;
    float c0[4] = {0.f, 0.f, 0.f, 0.f}, c1[4] = {0.f, 0.f, 0.f, 0.f};
#pragma unroll
    for (int ks = 0; ks < 4; ks++) {
        const uint32_t b0 = __shfl_sync(0xffffffffu, pk, 8 * ks + t4);
        const uint32_t b1 = __shfl_sync(0xffffffffu, pk, 8 * ks + 4 + t4);
        mma16816(c0, a[ks][0], a[ks][1], a[ks][2], a[ks][3], b0, b1);
        mma16816(c1, a[4 + ks][0], a[4 + ks][1], a[4 + ks][2], a[4 + ks][3], b0, b1);
    }
    if (t4 == 0) { red[wa * 32 + g] = c0[0]; red[wa * 32 + 8 + g] = c0[2]; }
    if (t4 == 1) { red[wa * 32 + 16 + g] = c1[0]; red[wa * 32 + 24 + g] = c1[2]; }
}

__global__ void __launch_bounds__(NTHREADS, 1)
fused_kernel(const __grid_constant__ CUtensorMap tmK, const __grid_constant__ CUtensorMap tmV,
             const __grid_constant__ CUtensorMap tmG, const __grid_constant__ CUtensorMap tmU,
             const __grid_constant__ CUtensorMap tmM, const __grid_constant__ CUtensorMap tmQ,
             const __grid_constant__ CUtensorMap tmO, const __grid_constant__ CUtensorMap tmD,
             const __nv_bfloat16* __restrict__ x_in, const __nv_bfloat16* __restrict__ c_in,
             __nv_bfloat16* __restrict__ out)
{
    extern __shared__ __align__(1024) uint8_t smem[];
    const uint32_t sb = smem_u32(smem);
    const int tid = threadIdx.x, warp = tid >> 5, lane = tid & 31;
    const int b = blockIdx.x, G = gridDim.x;
    const uint32_t bars = sb + SM_BAR;
    const int at = tid - (NCONS + 32);

#ifdef EXIT_AT_ENTRY
    if (EXIT_AT_ENTRY == 2 && b < N_FIN_CTA && tid < 8) out[b * 8 + tid] = x_in[b * 8 + tid];
    if (EXIT_AT_ENTRY == 3 && b < N_FIN_CTA && tid < 8) out[b * 8 + tid] = __float2bfloat16_rn(1.0f);
    if (EXIT_AT_ENTRY == 4 && b < 36 && tid < 16) out[b * 16 + tid] = __float2bfloat16_rn(1.0f);
    if (out != nullptr) return;
#endif
    if (tid == 0) TS(24);
    uint32_t x2pk = 0, c2pk = 0, epoch_raw = 0;
    if (warp == 4) {
        if (lane == 0) {
            if (sb & 1023u) __trap();
#pragma unroll
            for (int s = 0; s < NSLOT; s++) { mbar_init(bars + B_FULL + s * 8, 1); mbar_init(bars + B_EMPTY + s * 8, 4); }
            mbar_init(bars + B_QRDY, NAUX / 32);
            mbar_init(bars + B_JOB, 1);
            mbar_init(bars + B_WO, 1);
            mbar_init(bars + B_G, 1);
            mbar_init(bars + B_U, 1);
#pragma unroll
            for (int s = 0; s < LATE_WIN; s++) mbar_init(bars + B_PACE + s * 8, 1);
            mbar_init(bars + B_DOWN, 2);
            mbar_init(bars + B_WM, 1);
            mbar_init(bars + B_WQ, 1);
            mbar_init(bars + B_FREE, LATE_GATE ? 2 : 1);
            asm volatile("fence.mbarrier_init.release.cluster;" ::: "memory");
            fence_async_smem();
            if (b < N_MOD_CTA) {
                mbar_expect_tx(bars + B_WM, D_MODEL * 64);
#pragma unroll
                for (int r = 0; r < 3; r++) tma2d(sb + SM_U + r * 192 * 64, &tmM, b * 32, r * 192, bars + B_WM);
            }
            if (b < N_Q_CTA) {
                mbar_expect_tx(bars + B_WQ, D_MODEL * 64);
#pragma unroll
                for (int r = 0; r < 3; r++) tma2d(sb + SM_D + r * 192 * 64, &tmQ, b * 32, r * 192, bars + B_WQ);
            }
            TS(0);
        }
    } else {
        epoch_raw = ld_poll1(&g_s.epoch[0]);
        if (warp >= 5) {
            c2pk = *reinterpret_cast<const uint32_t*>(c_in + 2 * at);
            x2pk = *reinterpret_cast<const uint32_t*>(x_in + 2 * at);
            if (at < 32) {
                if (b < N_MOD_CTA) st_pub1(&g_s.mod[b * 32 + at], 0u);
                if (b < N_Q_CTA) st_pub1(&g_s.q[b * 32 + at], 0u);
            }
        } else {
            const int hq = tid >> 6, d = (tid & 63) * 2;
            st_pub2(&g_s.po[0][hq * 4 + (d >> 5)][b][d & 31], 0u, 0u);
            if ((d & 31) < 8) st_pub2(&g_s.po[0][hq * 4 + (d >> 5)][b][32 + (d & 31)], 0u, 0u);
        }
    }
    __syncthreads();

    if (warp == 4) {
        if (lane == 0) {
            volatile int* s_tile = reinterpret_cast<volatile int*>(smem + SM_BAR + B_TILE);
            const uint64_t pol = policy_evict_first();
            constexpr int NSTAT = (NSLOT + 1) / 2;
            int t, tn;
            if (NSLOT & 1) { t = (NSTAT - 1) * G + b; tn = (int)atomicAdd(&g_s.ctr[0], 1u) + NSTAT * G; }
            else           { t = (int)atomicAdd(&g_s.ctr[0], 1u) + NSTAT * G; tn = 0; }
            auto first_item = [&](int i) {
                const int ti = (i >> 1) * G + b;
                if (!(i & 1)) s_tile[i] = ti / TPH;
                mbar_expect_tx(bars + B_FULL + i * 8, SLOT_BYTES);
                tma3d(sb + SM_RING + i * SLOT_BYTES, (i & 1) ? &tmV : &tmK, ti * TILE, bars + B_FULL + i * 8, pol);
            };
            if (START_PACE >= 1 && b < N_MOD_CTA) mbar_wait(bars + B_WM, 0);
            first_item(0);
            if (START_PACE < 2) first_item(1);
            if (START_PACE >= 1 && b < N_Q_CTA) mbar_wait(bars + B_WQ, 0);
            if (START_PACE >= 2) first_item(1);
#pragma unroll
            for (int i = 2; i < NSLOT; i++) first_item(i);
            if (b < N_FFN_CTA) {
                mbar_expect_tx(bars + B_G, SM_GSZ);
#pragma unroll
                for (int r = 0; r < 3; r++) {
                    if (START_PACE >= 1) mbar_wait(bars + B_FULL + r * 8, 0);
                    tma2d(sb + SM_G + r * 192 * 80, &tmG, b * FCOLS, r * 192, bars + B_G);
                }
            }
            TS(23);
            if (PF_ITEMS > 0) {
                if (PF_WHEN == 1 && b < N_FFN_CTA) mbar_wait(bars + B_G, 0);
                TS(25);
                if (NSLOT & 1) tma3d_prefetch(&tmV, t * TILE, pol);
                if (PF_ITEMS > 1 && (NSLOT & 1)) { tma3d_prefetch(&tmK, tn * TILE, pol); tma3d_prefetch(&tmV, tn * TILE, pol); }
                if (PF_ITEMS > 1 && !(NSLOT & 1)) { tma3d_prefetch(&tmK, t * TILE, pol); tma3d_prefetch(&tmV, t * TILE, pol); }
            }
            int s = 0;
            uint32_t ph = 0;
            bool skipK = (NSLOT & 1);
            while (true) {
                if (!skipK) {
                    tn = (int)atomicAdd(&g_s.ctr[0], 1u) + NSTAT * G;
                    mbar_wait(bars + B_EMPTY + s * 8, ph);
                    if (t >= NT) {
                        if (tn < t) __trap();
                        s_tile[s] = -1; mbar_arrive(bars + B_FULL + s * 8);
                        break;
                    }
                    s_tile[s] = t / TPH;
                    mbar_expect_tx(bars + B_FULL + s * 8, SLOT_BYTES);
                    tma3d(sb + SM_RING + s * SLOT_BYTES, &tmK, t * TILE, bars + B_FULL + s * 8, pol);
                    if (++s == NSLOT) { s = 0; ph ^= 1; }
                }
                skipK = false;
                mbar_wait(bars + B_EMPTY + s * 8, ph);
                mbar_expect_tx(bars + B_FULL + s * 8, SLOT_BYTES);
                tma3d(sb + SM_RING + s * SLOT_BYTES, &tmV, t * TILE, bars + B_FULL + s * 8, pol);
                if (++s == NSLOT) { s = 0; ph ^= 1; }
                t = tn;
            }
            TS(1);
            if (b < N_FFN_CTA && !EXP_NOLATE) {
                mbar_wait(bars + B_FREE, 0);
                constexpr int UB = (LATE_MODE == 0) ? 9 : 0;
                constexpr int NBOX = UB + 9 - DE_GROUPS;
                if (LATE_MODE != 0) {
                    mbar_expect_tx(bars + B_U, SM_GSZ);
#pragma unroll 1
                    for (int i = 0; i < 9; i++) tma2d(sb + SM_U + i * SM_DGRP, &tmU, b * FCOLS, i * 64, bars + B_U);
                    if (LATE_MODE == 2) mbar_wait(bars + B_U, 0);
                }
                int w = 0;
                uint32_t wp = 0;
#pragma unroll 1
                for (int i = 0; i < NBOX + LATE_WIN; i++) {
                    const uint32_t pb = bars + B_PACE + w * 8;
                    if (i >= LATE_WIN) {
                        mbar_wait(pb, wp ^ 1);
                        if (LATE_MODE == 0 && i - LATE_WIN == 8) mbar_arrive(bars + B_U);
                    }
                    if (i < NBOX) {
                        mbar_expect_tx(pb, SM_DGRP);
                        if (i < UB) tma2d(sb + SM_U + i * SM_DGRP, &tmU, b * FCOLS, i * 64, pb);
                        else tma2d(sb + SM_D + (i - UB + DE_GROUPS) * SM_DGRP, &tmD, (i - UB + DE_GROUPS) * 64, b * FCOLS, pb);
                    }
                    if (++w == LATE_WIN) { w = 0; wp ^= 1; }
                }
                mbar_arrive(bars + B_DOWN);
            }
        }
        return;
    }

    const uint32_t tag = epoch_raw + 1u;

    if (warp < 4) {
        const int tid_o = tid, b_o = b;
#pragma unroll 1
        for (int pass = (DRY_CONS && b < N_FFN_CTA) ? 0 : 1; pass < 2; pass++) {
        const bool real = DRY_CONS ? opaque(pass) != 0 : true;
        const int tid = DRY_CONS ? opaque(tid_o) : tid_o, b = DRY_CONS ? opaque(b_o) : b_o;
        const int warp = tid >> 5, lane = tid & 31, g = lane >> 2, t4 = lane & 3, mi = lane >> 3;
        if (real) {
        const volatile int* s_tile = reinterpret_cast<const volatile int*>(smem + SM_BAR + B_TILE);
        uint32_t offK[2], offV[2];
        {
            const int keyK = warp * 16 + (lane & 7) + ((lane >> 3) & 1) * 8, hiK = lane >> 4;
            const int keyV = warp * 16 + (lane & 7) + (lane >> 4) * 8, hiV = (lane >> 3) & 1;
#pragma unroll
            for (int h = 0; h < 2; h++) {
                offK[h] = keyK * 256 + h * 128 + ((hiK ^ ((keyK * 2 + h) & 7)) << 4);
                offV[h] = keyV * 256 + h * 128 + ((hiV ^ ((keyV * 2 + h) & 7)) << 4);
            }
        }
        float acc[8][4];
#pragma unroll
        for (int i = 0; i < 8; i++) { acc[i][0] = acc[i][1] = acc[i][2] = acc[i][3] = 0.f; }
        uint32_t mrun = M_INIT;
        float l0 = 0.f, l1 = 0.f;
        uint32_t qb[8][2];
        int cur = 0;
        int fpar = 0;
        const int jobhead = (b < N_JOB_CTA) ? (b >> 3) : -1;

        auto load_q = [&](int h) {
            const uint32_t* q32 = reinterpret_cast<const uint32_t*>(smem + SM_Q) + (2 * h + (g & 1)) * 64 + t4;
#pragma unroll
            for (int ks = 0; ks < 8; ks++) { qb[ks][0] = q32[ks * 8]; qb[ks][1] = q32[ks * 8 + 4]; }
        };
        auto flush = [&](int h) {
            float* fb = reinterpret_cast<float*>(smem + SM_FB) + (fpar * 4 + warp) * 256;
            float* fml = reinterpret_cast<float*>(smem + SM_FML) + fpar * 16;
            float la = l0, lb = l1;
#pragma unroll
            for (int o = 4; o < 32; o <<= 1) { la += __shfl_xor_sync(0xffffffffu, la, o); lb += __shfl_xor_sync(0xffffffffu, lb, o); }
#pragma unroll
            for (int i = 0; i < 8; i++) {
                if ((i >> 1) == t4) {
                    fb[16 * i + g] = acc[i][0];           fb[128 + 16 * i + g] = acc[i][1];
                    fb[16 * i + g + 8] = acc[i][2];       fb[128 + 16 * i + g + 8] = acc[i][3];
                }
            }
            if (lane == 0) {
                fml[warp * 4 + 0] = bf_lo(mrun); fml[warp * 4 + 1] = la;
                fml[warp * 4 + 2] = bf_hi(mrun); fml[warp * 4 + 3] = lb;
            }
            bar_sync(1, NCONS);
            if (tid == 0 && h == jobhead) mbar_arrive(bars + B_JOB);
            if (tid == 0) TS(32 + h);
            {
                const int hq = tid >> 6, d = (tid & 63) * 2;
                const float* f0 = reinterpret_cast<const float*>(smem + SM_FB) + fpar * 1024 + hq * 128 + d;
                float mw[4], M = -3.4e38f;
#pragma unroll
                for (int w = 0; w < 4; w++) { mw[w] = fml[w * 4 + hq * 2]; M = fmaxf(M, mw[w]); }
                float o0 = 0.f, o1 = 0.f, L = 0.f;
#pragma unroll
                for (int w = 0; w < 4; w++) {
                    const float sc = ex2((mw[w] - M) * LOG2E);
                    const float2 v = *reinterpret_cast<const float2*>(f0 + w * 256);
                    o0 = fmaf(sc, v.x, o0); o1 = fmaf(sc, v.y, o1);
                    L = fmaf(sc, fml[w * 4 + hq * 2 + 1], L);
                }
                uint32_t* prow = &g_s.po[h][hq * 4 + (d >> 5)][b][d & 31];
                st_pub2(prow, tagf(o0, tag), tagf(o1, tag));
                if ((d & 31) < 8) st_pub2(prow + 32, tagf(M, tag), tagf(L, tag));
                if (h + 1 < HKV) {
                    st_pub2(prow + 8 * MAXG * PROW, 0u, 0u);
                    if ((d & 31) < 8) st_pub2(prow + 8 * MAXG * PROW + 32, 0u, 0u);
                }
                if (h == HKV - 2) {
                    uint32_t* row = (b < N_FFN_CTA) ? g_s.y2[b] : (b >= 120 && b < N_JOB_CTA) ? g_s.y[HKV - 1][b - 120] : nullptr;
                    if (row) {
                        st_pub4(row + tid * 4, 0u);
                        if (tid < 16) st_pub4(row + 512 + tid * 4, 0u);
                    }
                }
            }
            fpar ^= 1;
#pragma unroll
            for (int i = 0; i < 8; i++) { acc[i][0] = acc[i][1] = acc[i][2] = acc[i][3] = 0.f; }
            mrun = M_INIT; l0 = 0.f; l1 = 0.f;
        };

        mbar_wait(bars + B_QRDY, 0);
        if (tid == 0) TS(2);
        load_q(0);
        int s = 0;
        uint32_t ph = 0;
        while (true) {
            mbar_wait(bars + B_FULL + s * 8, ph);
            const int h = s_tile[s];
            if (h < 0) break;
            if (h != cur) {
                for (; cur < h; cur++) flush(cur);
                load_q(h);
            }
            const uint32_t kbase = sb + SM_RING + s * SLOT_BYTES;
            float sa[4] = {0.f, 0.f, 0.f, 0.f}, sc2[4] = {0.f, 0.f, 0.f, 0.f};
            {
                uint32_t a[8][4];
#pragma unroll
                for (int ks = 0; ks < 8; ks++) ldsm4(a[ks], (kbase + offK[ks >> 2]) ^ ((ks & 3) << 5));
#pragma unroll
                for (int ks = 0; ks < 8; ks += 2) {
                    mma16816(sa, a[ks][0], a[ks][1], a[ks][2], a[ks][3], qb[ks][0], qb[ks][1]);
                    mma16816(sc2, a[ks + 1][0], a[ks + 1][1], a[ks + 1][2], a[ks + 1][3], qb[ks + 1][0], qb[ks + 1][1]);
                }
            }
            __syncwarp();
            if (lane == 0) mbar_arrive(bars + B_EMPTY + s * 8);
            if (++s == NSLOT) { s = 0; ph ^= 1; }
            uint32_t s01 = pack_bf16(sa[0] + sc2[0], sa[1] + sc2[1]);
            uint32_t s23 = pack_bf16(sa[2] + sc2[2], sa[3] + sc2[3]);
            s01 = pack_bf16(bf_lo(s01) * QK_SCALE, bf_hi(s01) * QK_SCALE);
            s23 = pack_bf16(bf_lo(s23) * QK_SCALE, bf_hi(s23) * QK_SCALE);
            uint32_t mx = max_bf16x2(s01, s23);
            mx = max_bf16x2(mx, __shfl_xor_sync(0xffffffffu, mx, 4));
            mx = max_bf16x2(mx, __shfl_xor_sync(0xffffffffu, mx, 8));
            mx = max_bf16x2(mx, __shfl_xor_sync(0xffffffffu, mx, 16));
            const uint32_t mnew = max_bf16x2(mrun, mx);
            if (mnew != mrun) {
                const float a0 = ex2((bf_lo(mrun) - bf_lo(mnew)) * LOG2E);
                const float a1 = ex2((bf_hi(mrun) - bf_hi(mnew)) * LOG2E);
                l0 *= a0; l1 *= a1;
#pragma unroll
                for (int i = 0; i < 8; i++) { acc[i][0] *= a0; acc[i][1] *= a1; acc[i][2] *= a0; acc[i][3] *= a1; }
                mrun = mnew;
            }
            const float m0 = bf_lo(mrun), m1 = bf_hi(mrun);
            const float p0 = ex2((bf_lo(s01) - m0) * LOG2E), p1 = ex2((bf_hi(s01) - m1) * LOG2E);
            const float p2 = ex2((bf_lo(s23) - m0) * LOG2E), p3 = ex2((bf_hi(s23) - m1) * LOG2E);
            l0 += p0 + p2; l1 += p1 + p3;
            const uint32_t pb0 = movmatrix_t(pack_bf16(p0, p1));
            const uint32_t pb1 = movmatrix_t(pack_bf16(p2, p3));
            mbar_wait(bars + B_FULL + s * 8, ph);
            {
                const uint32_t vbase = sb + SM_RING + s * SLOT_BYTES;
                uint32_t v[8][4];
#pragma unroll
                for (int i = 0; i < 8; i++) ldsm4t(v[i], (vbase + offV[i >> 2]) ^ ((i & 3) << 5));
#pragma unroll
                for (int i = 0; i < 8; i++) mma16816(acc[i], v[i][0], v[i][1], v[i][2], v[i][3], pb0, pb1);
            }
            __syncwarp();
            if (lane == 0) mbar_arrive(bars + B_EMPTY + s * 8);
            if (++s == NSLOT) { s = 0; ph ^= 1; }
        }
        if (tid == 0) TS(3);
        if (LATE_GATE == 1 && tid == 0) mbar_arrive(bars + B_FREE);
        for (; cur < HKV; cur++) flush(cur);
        if (tid == 0) TS(4);
        if (LATE_GATE == 2 && tid == 0) mbar_arrive(bars + B_FREE);
        if (LATE_GATE == 3 && tid == 127) {
            unsigned it = 0;
            while (((ld_poll1(&g_s.po[HKV - 1][7][b][31]) ^ tag) & 3u) && ++it < SPIN_MAX) {}
            mbar_arrive(bars + B_FREE);
        }
        if (b >= N_FFN_CTA) break;
        }
        {
            uint32_t da[9][10];
            if (real && !EXP_NOLATE) mbar_wait(bars + B_DOWN, 0);
#pragma unroll
            for (int i = 0; i < 9; i++) {
                const int mt = warp * 9 + i;
                const int c = 2 * (mt & 3) + (mi & 1);
                const uint32_t base = sb + SM_D + (mt >> 2) * SM_DGRP;
                const int r0 = (lane & 7) + (mi >> 1) * 8, r2 = 32 + (lane & 7);
                uint32_t f[4];
                ldsm4t(f, base + r0 * 128 + ((c ^ (r0 & 7)) << 4));
                da[i][0] = f[0]; da[i][1] = f[1]; da[i][2] = f[2]; da[i][3] = f[3];
                ldsm4t(f, base + (r0 + 16) * 128 + ((c ^ (r0 & 7)) << 4));
                da[i][4] = f[0]; da[i][5] = f[1]; da[i][6] = f[2]; da[i][7] = f[3];
                ldsm2t(da[i][8], da[i][9], base + r2 * 128 + ((c ^ (r2 & 7)) << 4));
            }
            if (tid == 0) TS(19);
            if (real) bar_sync(3, NCONS + 64);
            const uint32_t* acts = reinterpret_cast<const uint32_t*>(smem + X_ACT);
            const uint32_t b00 = acts[t4], b01 = acts[4 + t4], b10 = acts[8 + t4], b11 = acts[12 + t4], b20 = acts[16 + t4];
            float y[9][4];
#pragma unroll
            for (int i = 0; i < 9; i++) {
                y[i][0] = y[i][1] = y[i][2] = y[i][3] = 0.f;
                mma16816(y[i], da[i][0], da[i][1], da[i][2], da[i][3], b00, b01);
            }
#pragma unroll
            for (int i = 0; i < 9; i++) mma16816(y[i], da[i][4], da[i][5], da[i][6], da[i][7], b10, b11);
#pragma unroll
            for (int i = 0; i < 9; i++) mma1688(y[i], da[i][8], da[i][9], b20);
            uint32_t* row = g_s.y2[b] + warp * 144 + g;
#pragma unroll
            for (int q = 0; q < 3; q++) {
                float r0 = y[4 * q][0], r1 = y[4 * q][2];
#pragma unroll
                for (int j = 1; j < 4; j++) if (4 * q + j < 9 && t4 == j) { r0 = y[4 * q + j][0]; r1 = y[4 * q + j][2]; }
                if (real && 4 * q + t4 < 9) {
                    st_pub1(row + (4 * q + t4) * 16, tagf(r0, tag));
                    st_pub1(row + (4 * q + t4) * 16 + 8, tagf(r1, tag));
                }
            }
            if (tid == 0) TS(16);
        }
        }
        return;
    }

    const int wa = at >> 5;
    if (at == 0) TS(5);
    const float x0 = bf_lo(x2pk), x1 = bf_hi(x2pk);
    float mean1, rsd1;
    ln_stats(x0, x1, reinterpret_cast<float*>(smem + X_ST1), at, mean1, rsd1);
    {
        uint32_t fa[8][4];
        float* red0 = reinterpret_cast<float*>(smem + X_RED0);
        float* red1 = reinterpret_cast<float*>(smem + X_RED1);
        if (b < N_MOD_CTA) {
            const uint32_t cpk = pack_bf16(silu_f(bf_lo(c2pk)), silu_f(bf_hi(c2pk)));
            mbar_wait(bars + B_WM, 0);
            if (at == 0) TS(20);
            load_frag32(fa, sb + SM_U, wa, lane);
            gemv32(fa, cpk, red0, wa, lane);
            bar_sync(2, NAUX);
            if (at < 32) {
                const float sum = sum9(red0 + at, 32);
                st_pub1(&g_s.mod[b * 32 + at], __float_as_uint(bfr(sum)) | tag);
            }
        }
        if (at == 0) TS(6);
        if (b < N_Q_CTA) {
            mbar_wait(bars + B_WQ, 0);
            if (at == 0) TS(21);
            load_frag32(fa, sb + SM_D, wa, lane);
            uint2 sa2, ca2;
            unsigned it = 0;
            do {
                sa2 = ld_poll2(&g_s.mod[2 * at]);
                ca2 = ld_poll2(&g_s.mod[D_MODEL + 2 * at]);
                if (++it > SPIN_MAX) __trap();
            } while (bad2(sa2, tag) | bad2(ca2, tag));
            const uint32_t hpk = modulate2(x0, x1, mean1, rsd1, ca2, sa2);
            if (at == 0) TS(7);
            gemv32(fa, hpk, red1, wa, lane);
            bar_sync(2, NAUX);
            if (at < 32) {
                const float sum = sum9(red1 + at, 32);
                st_pub1(&g_s.q[b * 32 + at], __float_as_uint(bfr(sum)) | tag);
            }
        } else {
            const long long t0 = clock64();
            while (clock64() - t0 < 5000) __nanosleep(200);
        }
    }
    {
        uint4 v[4];
        unsigned it = 0;
        uint32_t pend = (at + 3 * NAUX < 1024) ? 15u : 7u;
        do {
#pragma unroll
            for (int r = 0; r < 4; r++) if (pend & (1u << r)) v[r] = ld_poll4(&g_s.q[(at + r * NAUX) * 4]);
#pragma unroll
            for (int r = 0; r < 4; r++) if ((pend & (1u << r)) && !bad4(v[r], tag)) pend &= ~(1u << r);
            if (++it > SPIN_MAX) __trap();
        } while (pend);
        uint2* q_s = reinterpret_cast<uint2*>(smem + SM_Q);
#pragma unroll
        for (int r = 0; r < 4; r++) {
            const int idx = at + r * NAUX;
            if (idx < 1024) q_s[idx] = make_uint2((v[r].x >> 16) | (v[r].y & 0xffff0000u), (v[r].z >> 16) | (v[r].w & 0xffff0000u));
        }
        __syncwarp();
        if (lane == 0) mbar_arrive(bars + B_QRDY);
    }
    if (at == 0) TS(8);
    if (b >= N_JOB_CTA) return;
    if (at == 64) {
        fence_async_smem();
        mbar_expect_tx(bars + B_WO, 9 * SM_OGRP);
#pragma unroll
        for (int j = 0; j < 9; j++) tma2d(sb + SM_D + j * SM_OGRP, &tmO, j * 64, b * 32, bars + B_WO);
    }

    const int at_o = at, b_o = b;
#pragma unroll 1
    for (int pass = DRY_AUX ? 0 : 1; pass < 2; pass++) {
    const bool real = DRY_AUX ? opaque(pass) != 0 : true;
    const int at = DRY_AUX ? opaque(at_o) : at_o, b = DRY_AUX ? opaque(b_o) : b_o;
    const int lane = at & 31, wa = at >> 5, g = lane >> 2, t4 = lane & 3, mi = lane >> 3;
    {
        const int h = b >> 3, sl = b & 7;
        float* jred = reinterpret_cast<float*>(smem + X_RED0);
        float* jml = reinterpret_cast<float*>(smem + X_JML);
        uint32_t oa[8][4];
        if (real) mbar_wait_long(bars + B_WO, 0);
#pragma unroll
        for (int mt = 0; mt < 4; mt++) {
#pragma unroll
            for (int ks = 0; ks < 2; ks++) {
                const int r = ks * 16 + (lane & 7) + (mi >> 1) * 8, c = 2 * mt + (mi & 1);
                ldsm4t(oa[mt * 2 + ks], sb + SM_D + wa * SM_OGRP + r * 128 + ((c ^ (r & 7)) << 4));
            }
        }
        if (real && b < N_FFN_CTA) {
            bar_sync(2, NAUX);
            if (at == 0) {
                fence_async_smem();
                mbar_expect_tx(bars + B_DOWN, DE_GROUPS * SM_DGRP);
#pragma unroll
                for (int j = 0; j < DE_GROUPS; j++) tma2d(sb + SM_D + j * SM_DGRP, &tmD, j * 64, b * FCOLS, bars + B_DOWN);
                mbar_arrive(bars + B_FREE);
            }
        }
        const int ycol = wa * 64 + t4 * 16 + g;
        uint32_t yp0 = 0, yp1 = 0;
        if (real) {
            mbar_wait_long(bars + B_JOB, 0);
            if (h != HKV - 1) {
                const long long t0 = clock64();
                while (clock64() - t0 < JOB_DELAY_CLK) __nanosleep(400);
            }
        }
        if (at == 0) TS(9);
        const int v = at & 7, bl = at >> 3;
        uint4 o4[4];
        uint2 ml[4];
        {
            const uint32_t* pO = real ? &g_s.po[h][sl][0][0] : &g_s.q[0];
            const uint32_t* pY = ((real && h > 0) ? &g_s.y[h - 1][sl][0] : &g_s.q[0]) + ycol;
            const int rmask = real ? 255 : 63;
            uint32_t pend = 0;
#pragma unroll
            for (int r = 0; r < 4; r++) {
                o4[r] = make_uint4(0u, 0u, 0u, 0u); ml[r] = make_uint2(0u, 0x3f800000u);
                if (bl + 36 * r < G) pend |= 1u << r;
            }
            if (h > 0 || !real) pend |= 16u;
            unsigned it = 0;
            while (pend) {
#pragma unroll
                for (int r = 0; r < 4; r++) {
                    if (pend & (1u << r)) {
                        o4[r] = ld_poll4(pO + ((bl + 36 * r) & rmask) * PROW + v * 4);
                        ml[r] = ld_poll2(pO + ((bl + 36 * r) & rmask) * PROW + 32);
                    }
                }
                if (pend & 16u) {
                    yp0 = ld_poll1(pY);
                    yp1 = ld_poll1(pY + 8);
                }
#pragma unroll
                for (int r = 0; r < 4; r++)
                    if ((pend & (1u << r)) && !(bad4(o4[r], tag) | bad2(ml[r], tag))) pend &= ~(1u << r);
                if ((pend & 16u) && !(((yp0 ^ tag) | (yp1 ^ tag)) & 3u)) pend &= ~16u;
                if (++it > SPIN_MAX) __trap();
                if (pend && h != HKV - 1) __nanosleep(500);
            }
            __syncwarp();
        }
        if (at == 0) { TS(10); TC(58); }
        float Mw = -3.4e38f;
#pragma unroll
        for (int r = 0; r < 4; r++) if (bl + 36 * r < G) Mw = fmaxf(Mw, untag_bf(ml[r].x));
        Mw = fmaxf(Mw, __shfl_xor_sync(0xffffffffu, Mw, 8));
        Mw = fmaxf(Mw, __shfl_xor_sync(0xffffffffu, Mw, 16));
        float a4[4] = {0.f, 0.f, 0.f, 0.f}, ls = 0.f;
#pragma unroll
        for (int r = 0; r < 4; r++) {
            if (bl + 36 * r < G) {
                const float w = ex2((untag_bf(ml[r].x) - Mw) * LOG2E);
                a4[0] = fmaf(w, __uint_as_float(o4[r].x), a4[0]); a4[1] = fmaf(w, __uint_as_float(o4[r].y), a4[1]);
                a4[2] = fmaf(w, __uint_as_float(o4[r].z), a4[2]); a4[3] = fmaf(w, __uint_as_float(o4[r].w), a4[3]);
                ls = fmaf(w, __uint_as_float(ml[r].y), ls);
            }
        }
#pragma unroll
        for (int o = 8; o < 32; o <<= 1) {
#pragma unroll
            for (int j = 0; j < 4; j++) a4[j] += __shfl_xor_sync(0xffffffffu, a4[j], o);
            ls += __shfl_xor_sync(0xffffffffu, ls, o);
        }
        if (lane < 8) *reinterpret_cast<float4*>(&jred[wa * 32 + lane * 4]) = make_float4(a4[0], a4[1], a4[2], a4[3]);
        if (lane == 0) *reinterpret_cast<float2*>(&jml[wa * 2]) = make_float2(Mw, ls);
        if (at == 0) TC(59);
        bar_sync(2, NAUX);
        if (at == 0) TC(60);
        float2 mlw[9];
        float ow[9];
#pragma unroll
        for (int w = 0; w < 9; w++) { mlw[w] = *reinterpret_cast<const float2*>(&jml[2 * w]); ow[w] = jred[w * 32 + lane]; }
        const float M = fmaxf(fmaxf(fmaxf(fmaxf(mlw[0].x, mlw[1].x), fmaxf(mlw[2].x, mlw[3].x)),
                                    fmaxf(fmaxf(mlw[4].x, mlw[5].x), fmaxf(mlw[6].x, mlw[7].x))), mlw[8].x);
        float oe = 0.f, oo = 0.f, Le = 0.f, Lo = 0.f;
#pragma unroll
        for (int w = 0; w < 9; w++) {
            const float sc = ex2((mlw[w].x - M) * LOG2E);
            if (w & 1) { oo = fmaf(sc, ow[w], oo); Lo = fmaf(sc, mlw[w].y, Lo); }
            else       { oe = fmaf(sc, ow[w], oe); Le = fmaf(sc, mlw[w].y, Le); }
        }
        const float o = __fdividef(oe + oo, Le + Lo);
        if (at == 0) TC(61);
        const uint32_t opk = pack_bf16(o, __shfl_down_sync(0xffffffffu, o, 1));
        const uint32_t b00 = __shfl_sync(0xffffffffu, opk, 2 * t4), b01 = __shfl_sync(0xffffffffu, opk, 8 + 2 * t4);
        const uint32_t b10 = __shfl_sync(0xffffffffu, opk, 16 + 2 * t4), b11 = __shfl_sync(0xffffffffu, opk, 24 + 2 * t4);
        float y[4][4];
#pragma unroll
        for (int mt = 0; mt < 4; mt++) {
            y[mt][0] = y[mt][1] = y[mt][2] = y[mt][3] = 0.f;
            mma16816(y[mt], oa[2 * mt][0], oa[2 * mt][1], oa[2 * mt][2], oa[2 * mt][3], b00, b01);
        }
#pragma unroll
        for (int mt = 0; mt < 4; mt++)
            mma16816(y[mt], oa[2 * mt + 1][0], oa[2 * mt + 1][1], oa[2 * mt + 1][2], oa[2 * mt + 1][3], b10, b11);
        float r0 = y[0][0], r1 = y[0][2];
#pragma unroll
        for (int mt = 1; mt < 4; mt++) if (t4 == mt) { r0 = y[mt][0]; r1 = y[mt][2]; }
        if (h > 0) { r0 += __uint_as_float(yp0); r1 += __uint_as_float(yp1); }
        if (real) {
            st_pub1(&g_s.y[h][sl][ycol], tagf(r0, tag));
            st_pub1(&g_s.y[h][sl][ycol + 8], tagf(r1, tag));
        }
        if (at == 0) { TS(11); TC(62); }
    }
    if (b >= N_FFN_CTA) continue;

    uint2 ga2, sb2, cb2;
    {
        unsigned it = 0;
        do {
            ga2 = ld_poll2(&g_s.mod[2 * D_MODEL + 2 * at]);
            sb2 = ld_poll2(&g_s.mod[3 * D_MODEL + 2 * at]);
            cb2 = ld_poll2(&g_s.mod[4 * D_MODEL + 2 * at]);
            if (++it > SPIN_MAX) __trap();
        } while (bad2(ga2, tag) | bad2(sb2, tag) | bad2(cb2, tag));
    }
    uint32_t gbv = 0;
    if (b < N_FIN_CTA && at < 8) {
        unsigned it = 0;
        do { gbv = ld_poll1(&g_s.mod[5 * D_MODEL + b * 8 + at]); if (++it > SPIN_MAX) __trap(); } while ((gbv ^ tag) & 3u);
    }
    uint32_t gf[10][4], uf[10][4];
    if (real) mbar_wait_long(bars + B_G, 0);
#pragma unroll
    for (int j = 0; j < 5; j++) {
        ldsm4t(gf[2 * j], sb + SM_G + (wa * 64 + lane) * 80 + j * 16);
        ldsm4t(gf[2 * j + 1], sb + SM_G + (wa * 64 + 32 + lane) * 80 + j * 16);
    }
    auto load_u = [&]() {
#pragma unroll
        for (int j = 0; j < 5; j++) {
            ldsm4t(uf[2 * j], sb + SM_U + (wa * 64 + lane) * 80 + j * 16);
            ldsm4t(uf[2 * j + 1], sb + SM_U + (wa * 64 + 32 + lane) * 80 + j * 16);
        }
    };
    float* x2s = reinterpret_cast<float*>(smem + T_X2);
    float2* tgu = reinterpret_cast<float2*>(smem + T_GU);
    float* tfin = reinterpret_cast<float*>(smem + X_FIN);
    bool have_u = false;
    uint32_t hpk;
    {
        uint2 v[8];
        unsigned it = 0;
        uint32_t pend = 255u;
        const uint32_t* pY = (real ? &g_s.y[HKV - 1][0][0] : &g_s.q[0]) + 2 * at;
        const int ystride = real ? D_MODEL : 0;
#pragma unroll
        for (int r = 0; r < 8; r++) v[r] = make_uint2(0u, 0u);
        while (__any_sync(0xffffffffu, pend != 0)) {
#pragma unroll
            for (int r = 0; r < 8; r++) if (pend & (1u << r)) v[r] = ld_poll2(pY + r * ystride);
            if (!have_u && (!real || __all_sync(0xffffffffu, mbar_test(bars + B_U, 0)))) {
                load_u(); have_u = true;
                if (at == 0) TS(22);
            }
#pragma unroll
            for (int r = 0; r < 8; r++) if ((pend & (1u << r)) && !bad2(v[r], tag)) pend &= ~(1u << r);
            if (++it > SPIN_MAX) __trap();
        }
        if (at == 0) { TS(13); TC(48); }
        const float s0 = ((__uint_as_float(v[0].x) + __uint_as_float(v[1].x)) + (__uint_as_float(v[2].x) + __uint_as_float(v[3].x))) +
                         ((__uint_as_float(v[4].x) + __uint_as_float(v[5].x)) + (__uint_as_float(v[6].x) + __uint_as_float(v[7].x)));
        const float s1 = ((__uint_as_float(v[0].y) + __uint_as_float(v[1].y)) + (__uint_as_float(v[2].y) + __uint_as_float(v[3].y))) +
                         ((__uint_as_float(v[4].y) + __uint_as_float(v[5].y)) + (__uint_as_float(v[6].y) + __uint_as_float(v[7].y)));
        const uint32_t apk = pack_bf16(s0, s1);
        const uint32_t gpk = pack_bf16(untag_bf(ga2.x) * bf_lo(apk), untag_bf(ga2.y) * bf_hi(apk));
        const uint32_t ypk = pack_bf16(x0 + bf_lo(gpk), x1 + bf_hi(gpk));
        const float y0 = bf_lo(ypk), y1 = bf_hi(ypk);
        *reinterpret_cast<float2*>(&x2s[2 * at]) = make_float2(y0, y1);
        float mean2, rsd2;
        if (at == 0) TC(49);
        ln_stats(y0, y1, reinterpret_cast<float*>(smem + X_ST2), at, mean2, rsd2);
        if (at == 0) TC(50);
        hpk = modulate2(y0, y1, mean2, rsd2, cb2, sb2);
    }
    if (!have_u) {
        mbar_wait(bars + B_U, 0);
        __syncwarp();
        load_u();
        if (at == 0) TS(22);
    }
    if (at == 0) { TS(14); TC(51); }
    {
        float y[5][4];
#pragma unroll
        for (int j = 0; j < 5; j++) y[j][0] = y[j][1] = y[j][2] = y[j][3] = 0.f;
#pragma unroll
        for (int ks = 0; ks < 4; ks++) {
            const uint32_t b0 = __shfl_sync(0xffffffffu, hpk, 8 * ks + t4);
            const uint32_t b1 = __shfl_sync(0xffffffffu, hpk, 8 * ks + 4 + t4);
            const int hf = ks >> 1, e = (ks & 1) * 2;
#pragma unroll
            for (int j = 0; j < 5; j++)
                mma16816(y[j], gf[2 * j + hf][e], uf[2 * j + hf][e], gf[2 * j + hf][e + 1], uf[2 * j + hf][e + 1], b0, b1);
        }
#pragma unroll
        for (int j = 0; j < 5; j++)
            if (t4 == (j & 3)) tgu[wa * FCOLS + j * 8 + g] = make_float2(y[j][0], y[j][2]);
    }
    if (at == 0) TC(52);
    bar_sync(2, NAUX);
    if (at == 0) TC(53);
    if (wa < 2) {
        if (at < FCOLS) {
            float2 p[9];
#pragma unroll
            for (int w = 0; w < 9; w++) p[w] = tgu[w * FCOLS + at];
            const float gs = (((p[0].x + p[1].x) + (p[2].x + p[3].x)) + ((p[4].x + p[5].x) + (p[6].x + p[7].x))) + p[8].x;
            const float us = (((p[0].y + p[1].y) + (p[2].y + p[3].y)) + ((p[4].y + p[5].y) + (p[6].y + p[7].y))) + p[8].y;
            const uint32_t gu = pack_bf16(gs, us);
            const float a = bfr(silu_f(bf_lo(gu))) * bf_hi(gu);
            reinterpret_cast<__nv_bfloat16*>(smem + X_ACT)[at] = __float2bfloat16_rn(a);
        }
        if (real) bar_arrive(3, NCONS + 64);
        if (at == 0) { TS(15); TC(54); }
    }
    if (b < N_FIN_CTA) {
        float a4[4] = {0.f, 0.f, 0.f, 0.f};
        if (at < 2 * N_FFN_CTA) {
            const uint32_t* pF = real ? &g_s.y2[at >> 1][b * 8 + (at & 1) * 4] : &g_s.q[at * 4];
            uint4 v;
            unsigned it = 0;
            do { v = ld_poll4(pF); if (++it > SPIN_MAX) __trap(); } while (bad4(v, tag));
            a4[0] = __uint_as_float(v.x); a4[1] = __uint_as_float(v.y); a4[2] = __uint_as_float(v.z); a4[3] = __uint_as_float(v.w);
        }
        __syncwarp();
        if (at == 0) { TS(18); TC(55); }
        const bool u1 = lane & 2, u2 = lane & 4;
        float k0 = (u1 ? a4[2] : a4[0]) + __shfl_xor_sync(0xffffffffu, u1 ? a4[0] : a4[2], 2);
        float k1 = (u1 ? a4[3] : a4[1]) + __shfl_xor_sync(0xffffffffu, u1 ? a4[1] : a4[3], 2);
        float k = (u2 ? k1 : k0) + __shfl_xor_sync(0xffffffffu, u2 ? k0 : k1, 4);
        k += __shfl_xor_sync(0xffffffffu, k, 8);
        k += __shfl_xor_sync(0xffffffffu, k, 16);
        if (lane < 8) tfin[wa * 8 + (lane & 1) * 4 + (lane & 2) + ((lane >> 2) & 1)] = k;
        if (at == 0) TC(56);
        bar_sync(2, NAUX);
        if (at < 8) {
            float v[8];
#pragma unroll
            for (int w = 0; w < 8; w++) v[w] = tfin[w * 8 + at];
            const float sum = ((v[0] + v[1]) + (v[2] + v[3])) + ((v[4] + v[5]) + (v[6] + v[7]));
            const float r = x2s[b * 8 + at] + bfr(untag_bf(gbv) * bfr(sum));
            if (real) out[b * 8 + at] = __float2bfloat16_rn(r);
        }
        if (at == 0) { TS(17); TC(57); }
    }
    }
    if (b == 0 && at == 0) {
        g_s.ctr[0] = 0u;
        g_s.epoch[0] = (epoch_raw >= 2u) ? 0u : epoch_raw + 1u;
    }
}

typedef CUresult (*EncodeFn)(CUtensorMap*, CUtensorMapDataType, cuuint32_t, void*, const cuuint64_t*, const cuuint64_t*,
                             const cuuint32_t*, const cuuint32_t*, CUtensorMapInterleave, CUtensorMapSwizzle,
                             CUtensorMapL2promotion, CUtensorMapFloatOOBfill);

void make_2d(EncodeFn enc, CUtensorMap* m, void* base, uint64_t cols, uint64_t rows, uint32_t bcols, uint32_t brows,
             CUtensorMapSwizzle sw, CUtensorMapL2promotion pr) {
    cuuint64_t gd[2] = {cols, rows};
    cuuint64_t gs[1] = {cols * 2};
    cuuint32_t bx[2] = {bcols, brows};
    cuuint32_t es[2] = {1, 1};
    enc(m, CU_TENSOR_MAP_DATA_TYPE_BFLOAT16, 2, base, gd, gs, bx, es, CU_TENSOR_MAP_INTERLEAVE_NONE, sw, pr,
        CU_TENSOR_MAP_FLOAT_OOB_FILL_NONE);
}

}

extern "C" void kernel_launch(void* const* d_in, const int* in_sizes, int n_in, void* d_out, int out_size) {
    (void)in_sizes; (void)n_in; (void)out_size;
    static EncodeFn enc = nullptr;
    static int nsm = 0;
    if (!enc) {
        void* fn = nullptr;
        cudaDriverEntryPointQueryResult qr;
        cudaGetDriverEntryPoint("cuTensorMapEncodeTiled", &fn, cudaEnableDefault, &qr);
        enc = (EncodeFn)fn;
        int dev = 0;
        cudaGetDevice(&dev);
        cudaDeviceGetAttribute(&nsm, cudaDevAttrMultiProcessorCount, dev);
        cudaFuncSetAttribute(fused_kernel, cudaFuncAttributeMaxDynamicSharedMemorySize, SM_TOTAL);
    }
    if (!enc) return;

    CUtensorMap tmK, tmV, tmG, tmU, tmM, tmQ, tmO, tmD;
    {
        cuuint64_t gd[3] = {64, 2, (cuuint64_t)HKV * SK};
        cuuint64_t gs[2] = {128, 256};
        cuuint32_t bx[3] = {64, 2, TILE};
        cuuint32_t es[3] = {1, 1, 1};
        enc(&tmK, CU_TENSOR_MAP_DATA_TYPE_BFLOAT16, 3, d_in[1], gd, gs, bx, es, CU_TENSOR_MAP_INTERLEAVE_NONE,
            CU_TENSOR_MAP_SWIZZLE_128B, CU_TENSOR_MAP_L2_PROMOTION_NONE, CU_TENSOR_MAP_FLOAT_OOB_FILL_NONE);
        enc(&tmV, CU_TENSOR_MAP_DATA_TYPE_BFLOAT16, 3, d_in[2], gd, gs, bx, es, CU_TENSOR_MAP_INTERLEAVE_NONE,
            CU_TENSOR_MAP_SWIZZLE_128B, CU_TENSOR_MAP_L2_PROMOTION_NONE, CU_TENSOR_MAP_FLOAT_OOB_FILL_NONE);
    }
    make_2d(enc, &tmG, d_in[6], FF, D_MODEL, FCOLS, 192, CU_TENSOR_MAP_SWIZZLE_NONE, CU_TENSOR_MAP_L2_PROMOTION_L2_256B);
    make_2d(enc, &tmU, d_in[7], FF, D_MODEL, FCOLS, 64, CU_TENSOR_MAP_SWIZZLE_NONE, U_PROMO);
    make_2d(enc, &tmM, d_in[10], 6 * D_MODEL, D_MODEL, 32, 192, CU_TENSOR_MAP_SWIZZLE_64B, CU_TENSOR_MAP_L2_PROMOTION_L2_128B);
    make_2d(enc, &tmQ, d_in[3], 4096, D_MODEL, 32, 192, CU_TENSOR_MAP_SWIZZLE_64B, CU_TENSOR_MAP_L2_PROMOTION_L2_128B);
    make_2d(enc, &tmO, d_in[4], D_MODEL, 4096, 64, 32, CU_TENSOR_MAP_SWIZZLE_128B, CU_TENSOR_MAP_L2_PROMOTION_NONE);
    make_2d(enc, &tmD, d_in[8], D_MODEL, FF, 64, FCOLS, CU_TENSOR_MAP_SWIZZLE_128B, D_PROMO);

    int grid = nsm < MAXG ? nsm : MAXG;
    if (grid < N_JOB_CTA) return;
    fused_kernel<<<grid, NTHREADS, SM_TOTAL, cudaStreamPerThread>>>(
        tmK, tmV, tmG, tmU, tmM, tmQ, tmO, tmD, (const __nv_bfloat16*)d_in[0], (const __nv_bfloat16*)d_in[9],
        (__nv_bfloat16*)d_out);
}
```

```cpp
#include <cuda_runtime.h>
#include <cuda_bf16.h>
#include <cuda.h>
#include <stdint.h>

namespace {

constexpr int D_MODEL = 576;
constexpr int HKV = 16;
constexpr int SK = 65536;
constexpr int FF = 4608;
constexpr int TILE = 64;
constexpr int TPH = SK / TILE;
constexpr int NT = HKV * TPH;
#define EXP_NSLOT 3
constexpr int NSLOT = EXP_NSLOT;
constexpr int RING_SLOTS = 4;
constexpr int SLOT_BYTES = TILE * 256;
constexpr int MAXG = 144;
constexpr int N_MOD_CTA = 108;
constexpr int N_Q_CTA = 128;
constexpr int N_JOB_CTA = 128;
constexpr int N_FFN_CTA = 116;
constexpr int N_FIN_CTA = 72;
constexpr int FCOLS = 40;

#define JOB_DELAY_CLK 8000
#define START_WIN 3
#define LATE_WIN 4
#define DE_GROUPS 0

constexpr int NCONS = 128;
constexpr int NAUX = 288;
constexpr int NTHREADS = NCONS + 32 + NAUX;

constexpr int SM_RING = 0;
constexpr int SM_G = SM_RING + RING_SLOTS * SLOT_BYTES;
constexpr int SM_GSZ = D_MODEL * FCOLS * 2;
constexpr int SM_U = SM_G + SM_GSZ;
constexpr int SM_D = SM_U + SM_GSZ;
constexpr int SM_DGRP = FCOLS * 128;
constexpr int SM_OGRP = 32 * 128;
constexpr int SM_Q = SM_D + 9 * SM_DGRP;
constexpr int SM_FB = SM_Q + 8192;
constexpr int SM_FML = SM_FB + 8192;
constexpr int SM_X = SM_FML + 128;
constexpr int SM_T = SM_X + 4096;
constexpr int SM_BAR = SM_T + 6144;
constexpr int SM_TOTAL = SM_BAR + 256;
static_assert(SM_U % 1024 == 0 && SM_D % 1024 == 0, "swizzled regions must be 1024-aligned");
static_assert(SM_TOTAL <= 232448, "smem");
constexpr int X_ST1 = SM_X;
constexpr int X_ST2 = SM_X + 128;
constexpr int X_RED0 = SM_X + 256;
constexpr int X_RED1 = X_RED0 + 1152;
constexpr int X_JML = X_RED1 + 1152;
constexpr int X_ACT = X_JML + 128;
constexpr int X_FIN = X_ACT + 128;
constexpr int T_GU = SM_T;
constexpr int T_X2 = SM_T + 3072;
static_assert(X_FIN + 384 <= SM_T, "aux scratch");

constexpr int B_FULL = 0;
constexpr int B_EMPTY = 32;
constexpr int B_QRDY = 64;
constexpr int B_QALL = 112;
constexpr int B_JOB = 72;
constexpr int B_WO = 80;
constexpr int B_G = 88;
constexpr int B_U = 96;
constexpr int B_DOWN = 104;
constexpr int B_WM = 208;
constexpr int B_WQ = 232;
constexpr int B_FREE = 136;
constexpr int B_PACE = 144;
constexpr int B_TILE = 192;

constexpr unsigned SPIN_MAX = 1u << 21;

constexpr int PROW = 40;
struct Scratch {
    uint32_t mod[3456];
    uint32_t q[4096];
    uint32_t po[HKV][8][MAXG][PROW];
    uint32_t y[HKV][8][D_MODEL];
    uint32_t y2[N_FFN_CTA][D_MODEL];
    uint32_t ctr[32];
    uint32_t epoch[32];
};
__device__ __align__(128) Scratch g_s;

#define TS(i) do { } while (0)
#define TC(i) do { } while (0)

__device__ __forceinline__ uint32_t smem_u32(const void* p) { return (uint32_t)__cvta_generic_to_shared(p); }
__device__ __forceinline__ void mbar_init(uint32_t bar, uint32_t cnt) {
    asm volatile("mbarrier.init.shared::cta.b64 [%0], %1;" ::"r"(bar), "r"(cnt) : "memory");
}
__device__ __forceinline__ void mbar_expect_tx(uint32_t bar, uint32_t bytes) {
    asm volatile("mbarrier.arrive.expect_tx.shared::cta.b64 _, [%0], %1;" ::"r"(bar), "r"(bytes) : "memory");
}
__device__ __forceinline__ void mbar_arrive(uint32_t bar) {
    asm volatile("mbarrier.arrive.shared::cta.b64 _, [%0];" ::"r"(bar) : "memory");
}
__device__ __forceinline__ bool mbar_try(uint32_t bar, uint32_t parity) {
    uint32_t ok;
    asm volatile("{\n.reg .pred p;\nmbarrier.try_wait.parity.shared::cta.b64 p, [%1], %2;\nselp.u32 %0, 1, 0, p;\n}"
                 : "=r"(ok) : "r"(bar), "r"(parity) : "memory");
    return ok != 0;
}
__device__ __forceinline__ bool mbar_test(uint32_t bar, uint32_t parity) {
    uint32_t ok;
    asm volatile("{\n.reg .pred p;\nmbarrier.test_wait.parity.shared::cta.b64 p, [%1], %2;\nselp.u32 %0, 1, 0, p;\n}"
                 : "=r"(ok) : "r"(bar), "r"(parity) : "memory");
    return ok != 0;
}
__device__ __forceinline__ void mbar_wait(uint32_t bar, uint32_t parity) {
    if (mbar_try(bar, parity)) return;
    const long long t0 = clock64();
    while (!mbar_try(bar, parity)) {
        if (clock64() - t0 > (1ll << 31)) __trap();
    }
}
__device__ __forceinline__ void mbar_wait_long(uint32_t bar, uint32_t parity) {
    const long long t0 = clock64();
    while (true) {
        uint32_t ok;
        asm volatile("{\n.reg .pred p;\nmbarrier.try_wait.parity.shared::cta.b64 p, [%1], %2, %3;\nselp.u32 %0, 1, 0, p;\n}"
                     : "=r"(ok) : "r"(bar), "r"(parity), "r"(200000u) : "memory");
        if (ok) return;
        if (clock64() - t0 > (1ll << 31)) __trap();
    }
}
__device__ __forceinline__ void bar_sync(int id, int n) { asm volatile("bar.sync %0, %1;" ::"r"(id), "r"(n) : "memory"); }
__device__ __forceinline__ void bar_arrive(int id, int n) { asm volatile("bar.arrive %0, %1;" ::"r"(id), "r"(n) : "memory"); }
__device__ __forceinline__ void fence_async_smem() { asm volatile("fence.proxy.async.shared::cta;" ::: "memory"); }

__device__ __forceinline__ uint64_t policy_evict_first() {
    uint64_t p;
    asm volatile("createpolicy.fractional.L2::evict_first.b64 %0, 1.0;" : "=l"(p));
    return p;
}
__device__ __forceinline__ void tma3d(uint32_t dst, const CUtensorMap* m, int c2, uint32_t bar, uint64_t pol) {
    asm volatile("cp.async.bulk.tensor.3d.shared::cluster.global.mbarrier::complete_tx::bytes.L2::cache_hint [%0], [%1, {%3, %3, %4}], [%2], %5;"
                 ::"r"(dst), "l"(m), "r"(bar), "r"(0), "r"(c2), "l"(pol) : "memory");
}
__device__ __forceinline__ void tma3d_prefetch(const CUtensorMap* m, int c2, uint64_t pol) {
    asm volatile("cp.async.bulk.prefetch.tensor.3d.L2.global.tile.L2::cache_hint [%0, {%1, %1, %2}], %3;"
                 ::"l"(m), "r"(0), "r"(c2), "l"(pol) : "memory");
}
__device__ __forceinline__ void tma2d(uint32_t dst, const CUtensorMap* m, int c0, int c1, uint32_t bar) {
    asm volatile("cp.async.bulk.tensor.2d.shared::cluster.global.mbarrier::complete_tx::bytes [%0], [%1, {%3, %4}], [%2];"
                 ::"r"(dst), "l"(m), "r"(bar), "r"(c0), "r"(c1) : "memory");
}
__device__ __forceinline__ void ldsm4(uint32_t (&r)[4], uint32_t addr) {
    asm volatile("ldmatrix.sync.aligned.m8n8.x4.shared.b16 {%0,%1,%2,%3}, [%4];"
                 : "=r"(r[0]), "=r"(r[1]), "=r"(r[2]), "=r"(r[3]) : "r"(addr) : "memory");
}
__device__ __forceinline__ void ldsm4t(uint32_t (&r)[4], uint32_t addr) {
    asm volatile("ldmatrix.sync.aligned.m8n8.x4.trans.shared.b16 {%0,%1,%2,%3}, [%4];"
                 : "=r"(r[0]), "=r"(r[1]), "=r"(r[2]), "=r"(r[3]) : "r"(addr) : "memory");
}
__device__ __forceinline__ void ldsm2t(uint32_t& r0, uint32_t& r1, uint32_t addr) {
    asm volatile("ldmatrix.sync.aligned.m8n8.x2.trans.shared.b16 {%0,%1}, [%2];" : "=r"(r0), "=r"(r1) : "r"(addr) : "memory");
}
__device__ __forceinline__ void mma16816(float (&c)[4], uint32_t a0, uint32_t a1, uint32_t a2, uint32_t a3, uint32_t b0, uint32_t b1) {
    asm volatile("mma.sync.aligned.m16n8k16.row.col.f32.bf16.bf16.f32 {%0,%1,%2,%3}, {%4,%5,%6,%7}, {%8,%9}, {%0,%1,%2,%3};"
                 : "+f"(c[0]), "+f"(c[1]), "+f"(c[2]), "+f"(c[3])
                 : "r"(a0), "r"(a1), "r"(a2), "r"(a3), "r"(b0), "r"(b1));
}
__device__ __forceinline__ void mma1688(float (&c)[4], uint32_t a0, uint32_t a1, uint32_t b0) {
    asm volatile("mma.sync.aligned.m16n8k8.row.col.f32.bf16.bf16.f32 {%0,%1,%2,%3}, {%4,%5}, {%6}, {%0,%1,%2,%3};"
                 : "+f"(c[0]), "+f"(c[1]), "+f"(c[2]), "+f"(c[3])
                 : "r"(a0), "r"(a1), "r"(b0));
}
__device__ __forceinline__ uint32_t movmatrix_t(uint32_t a) {
    uint32_t d;
    asm volatile("movmatrix.sync.aligned.m8n8.trans.b16 %0, %1;" : "=r"(d) : "r"(a));
    return d;
}
__device__ __forceinline__ uint32_t pack_bf16(float lo, float hi) {
    uint32_t d;
    asm("cvt.rn.bf16x2.f32 %0, %1, %2;" : "=r"(d) : "f"(hi), "f"(lo));
    return d;
}
__device__ __forceinline__ float bf_lo(uint32_t v) { return __uint_as_float(v << 16); }
__device__ __forceinline__ float bf_hi(uint32_t v) { return __uint_as_float(v & 0xffff0000u); }
__device__ __forceinline__ float bfr(float x) { return bf_lo(pack_bf16(x, 0.f)); }
__device__ __forceinline__ uint32_t max_bf16x2(uint32_t a, uint32_t b) {
    uint32_t d;
    asm("max.bf16x2 %0, %1, %2;" : "=r"(d) : "r"(a), "r"(b));
    return d;
}
__device__ __forceinline__ float ex2(float x) {
    float y;
    asm("ex2.approx.ftz.f32 %0, %1;" : "=f"(y) : "f"(x));
    return y;
}
__device__ __forceinline__ float silu_f(float x) { return __fdividef(x, 1.0f + __expf(-x)); }

__device__ __forceinline__ uint4 ld_poll4(const uint32_t* p) {
    uint4 v;
    asm volatile("ld.relaxed.gpu.global.v4.u32 {%0,%1,%2,%3}, [%4];" : "=r"(v.x), "=r"(v.y), "=r"(v.z), "=r"(v.w) : "l"(p) : "memory");
    return v;
}
__device__ __forceinline__ uint2 ld_poll2(const uint32_t* p) {
    uint2 v;
    asm volatile("ld.relaxed.gpu.global.v2.u32 {%0,%1}, [%2];" : "=r"(v.x), "=r"(v.y) : "l"(p) : "memory");
    return v;
}
__device__ __forceinline__ uint32_t ld_poll1(const uint32_t* p) {
    uint32_t v;
    asm volatile("ld.relaxed.gpu.global.u32 %0, [%1];" : "=r"(v) : "l"(p) : "memory");
    return v;
}
__device__ __forceinline__ void st_pub1(uint32_t* p, uint32_t a) {
    asm volatile("st.relaxed.gpu.global.u32 [%0], %1;" ::"l"(p), "r"(a) : "memory");
}
__device__ __forceinline__ void st_pub2(uint32_t* p, uint32_t a, uint32_t b) {
    asm volatile("st.relaxed.gpu.global.v2.u32 [%0], {%1,%2};" ::"l"(p), "r"(a), "r"(b) : "memory");
}
__device__ __forceinline__ void st_pub4(uint32_t* p, uint32_t a) {
    asm volatile("st.relaxed.gpu.global.v4.u32 [%0], {%1,%1,%1,%1};" ::"l"(p), "r"(a) : "memory");
}
__device__ __forceinline__ uint32_t tagf(float v, uint32_t tag) { return (__float_as_uint(v) & ~3u) | tag; }
__device__ __forceinline__ uint32_t bad4(const uint4& v, uint32_t tag) { return ((v.x ^ tag) | (v.y ^ tag) | (v.z ^ tag) | (v.w ^ tag)) & 3u; }
__device__ __forceinline__ uint32_t bad2(const uint2& v, uint32_t tag) { return ((v.x ^ tag) | (v.y ^ tag)) & 3u; }
__device__ __forceinline__ float untag_bf(uint32_t v) { return __uint_as_float(v & 0xffff0000u); }

constexpr float LOG2E = 1.4426950408889634f;
constexpr float QK_SCALE = 0.08838834764831845f;
constexpr uint32_t M_INIT = 0xFF7FFF7Fu;

__device__ __forceinline__ void ln_stats(float x0, float x1, float* st, int at, float& mean_r, float& rsd) {
    const float piv = __shfl_sync(0xffffffffu, x0, 0);
    const float d0 = x0 - piv, d1 = x1 - piv;
    float s1 = d0 + d1, s2 = fmaf(d0, d0, d1 * d1);
#pragma unroll
    for (int o = 1; o < 32; o <<= 1) {
        s1 += __shfl_xor_sync(0xffffffffu, s1, o);
        s2 += __shfl_xor_sync(0xffffffffu, s2, o);
    }
    if ((at & 31) == 0)
        *reinterpret_cast<float2*>(&st[(at >> 5) * 2]) = make_float2(fmaf(s1, 1.0f / 64.0f, piv), fmaf(s1 * s1, -1.0f / 64.0f, s2));
    bar_sync(2, NAUX);
    float2 sw[9];
#pragma unroll
    for (int w = 0; w < 9; w++) sw[w] = *reinterpret_cast<const float2*>(&st[2 * w]);
    const float ms = (((sw[0].x + sw[1].x) + (sw[2].x + sw[3].x)) + ((sw[4].x + sw[5].x) + (sw[6].x + sw[7].x))) + sw[8].x;
    const float m2s = (((sw[0].y + sw[1].y) + (sw[2].y + sw[3].y)) + ((sw[4].y + sw[5].y) + (sw[6].y + sw[7].y))) + sw[8].y;
    const float mu = ms * (1.0f / 9.0f);
    float e[9];
#pragma unroll
    for (int w = 0; w < 9; w++) e[w] = sw[w].x - mu;
    const float dd = ((fmaf(e[0], e[0], e[1] * e[1]) + fmaf(e[2], e[2], e[3] * e[3])) +
                      (fmaf(e[4], e[4], e[5] * e[5]) + fmaf(e[6], e[6], e[7] * e[7]))) + e[8] * e[8];
    const float var = fmaxf(fmaf(64.f, dd, m2s), 0.f) * (1.0f / 576.0f);
    mean_r = bfr(mu);
    float sd;
    asm("sqrt.approx.f32 %0, %1;" : "=f"(sd) : "f"(bfr(bfr(var) + 1e-5f)));
    sd = bfr(sd);
    asm("rcp.approx.f32 %0, %1;" : "=f"(rsd) : "f"(sd));
}
__device__ __forceinline__ uint32_t modulate2(float x0, float x1, float mean_r, float rsd, uint2 scale, uint2 shift) {
    const uint32_t dpk = pack_bf16(x0 - mean_r, x1 - mean_r);
    const uint32_t npk = pack_bf16(bf_lo(dpk) * rsd, bf_hi(dpk) * rsd);
    const uint32_t cpk = pack_bf16(1.0f + untag_bf(scale.x), 1.0f + untag_bf(scale.y));
    const uint32_t mpk = pack_bf16(bf_lo(npk) * bf_lo(cpk), bf_hi(npk) * bf_hi(cpk));
    return pack_bf16(bf_lo(mpk) + untag_bf(shift.x), bf_hi(mpk) + untag_bf(shift.y));
}
__device__ __forceinline__ float sum9(const float* p, int stride) {
    float v[9];
#pragma unroll
    for (int w = 0; w < 9; w++) v[w] = p[w * stride];
    return (((v[0] + v[1]) + (v[2] + v[3])) + ((v[4] + v[5]) + (v[6] + v[7]))) + v[8];
}

__device__ __forceinline__ void load_frag32(uint32_t (&a)[8][4], uint32_t base, int wa, int lane) {
    const int mi = lane >> 3;
#pragma unroll
    for (int ks = 0; ks < 4; ks++) {
        const int r = wa * 64 + ks * 16 + (lane & 7) + (mi >> 1) * 8;
#pragma unroll
        for (int j = 0; j < 2; j++) {
            const int c = 2 * j + (mi & 1);
            ldsm4t(a[j * 4 + ks], base + r * 64 + ((c ^ ((r >> 1) & 3)) << 4));
        }
    }
}
__device__ __forceinline__ void gemv32(const uint32_t (&a)[8][4], uint32_t pk, float* red, int wa, int lane) {
    const int g = lane >> 2, t4 = lane & 3;
    float c0[4] = {0.f, 0.f, 0.f, 0.f}, c1[4] = {0.f, 0.f, 0.f, 0.f};
#pragma unroll
    for (int ks = 0; ks < 4; ks++) {
        const uint32_t b0 = __shfl_sync(0xffffffffu, pk, 8 * ks + t4);
        const uint32_t b1 = __shfl_sync(0xffffffffu, pk, 8 * ks + 4 + t4);
        mma16816(c0, a[ks][0], a[ks][1], a[ks][2], a[ks][3], b0, b1);
        mma16816(c1, a[4 + ks][0], a[4 + ks][1], a[4 + ks][2], a[4 + ks][3], b0, b1);
    }
    if (t4 == 0) { red[wa * 32 + g] = c0[0]; red[wa * 32 + 8 + g] = c0[2]; }
    if (t4 == 1) { red[wa * 32 + 16 + g] = c1[0]; red[wa * 32 + 24 + g] = c1[2]; }
}

__global__ void __launch_bounds__(NTHREADS, 1)
fused_kernel(const __grid_constant__ CUtensorMap tmK, const __grid_constant__ CUtensorMap tmV,
             const __grid_constant__ CUtensorMap tmG, const __grid_constant__ CUtensorMap tmU,
             const __grid_constant__ CUtensorMap tmM, const __grid_constant__ CUtensorMap tmQ,
             const __grid_constant__ CUtensorMap tmO, const __grid_constant__ CUtensorMap tmD,
             const __nv_bfloat16* __restrict__ x_in, const __nv_bfloat16* __restrict__ c_in,
             __nv_bfloat16* __restrict__ out)
{
    extern __shared__ __align__(1024) uint8_t smem[];
    const uint32_t sb = smem_u32(smem);
    const int tid = threadIdx.x, warp = tid >> 5, lane = tid & 31;
    const int b = blockIdx.x, G = gridDim.x;
    const uint32_t bars = sb + SM_BAR;
    const int at = tid - (NCONS + 32);

    if (tid == 0) TS(24);
    constexpr int NSTART = 6 + NSLOT + 3;
    auto start_box = [&](int i) {
        if (i < 3) {
            if (b < N_MOD_CTA) {
                mbar_expect_tx(bars + B_WM + i * 8, 192 * 64);
                tma2d(sb + SM_U + i * 192 * 64, &tmM, b * 32, i * 192, bars + B_WM + i * 8);
            }
        } else if (i < 6) {
            if (b < N_Q_CTA) {
                mbar_expect_tx(bars + B_WM + i * 8, 192 * 64);
                tma2d(sb + SM_D + (i - 3) * 192 * 64, &tmQ, b * 32, (i - 3) * 192, bars + B_WM + i * 8);
            }
        } else if (i < 6 + NSLOT) {
            const int k = i - 6, ti = (k >> 1) * G + b;
            if (!(k & 1)) reinterpret_cast<volatile int*>(smem + SM_BAR + B_TILE)[k] = ti / TPH;
            mbar_expect_tx(bars + B_FULL + k * 8, SLOT_BYTES);
            tma3d(sb + SM_RING + k * SLOT_BYTES, (k & 1) ? &tmV : &tmK, ti * TILE, bars + B_FULL + k * 8, policy_evict_first());
        } else if (b < N_FFN_CTA) {
            const int r = i - 6 - NSLOT;
            if (r == 0) mbar_expect_tx(bars + B_G, SM_GSZ);
            tma2d(sb + SM_G + r * 192 * 80, &tmG, b * FCOLS, r * 192, bars + B_G);
        }
    };
    auto start_wait = [&](int i) {
        if (i < 3) { if (b < N_MOD_CTA) mbar_wait(bars + B_WM + i * 8, 0); }
        else if (i < 6) { if (b < N_Q_CTA) mbar_wait(bars + B_WM + i * 8, 0); }
        else if (i < 6 + NSLOT) mbar_wait(bars + B_FULL + (i - 6) * 8, 0);
    };
    uint32_t x2pk = 0, c2pk = 0, epoch_raw = 0;
    if (warp == 4) {
        if (lane == 0) {
            if (sb & 1023u) __trap();
#pragma unroll
            for (int s = 0; s < NSLOT; s++) { mbar_init(bars + B_FULL + s * 8, 1); mbar_init(bars + B_EMPTY + s * 8, 4); }
            mbar_init(bars + B_QRDY, 2);
            mbar_init(bars + B_QALL, NAUX / 32);
            mbar_init(bars + B_JOB, 1);
            mbar_init(bars + B_WO, 1);
            mbar_init(bars + B_G, 1);
            mbar_init(bars + B_U, 1);
#pragma unroll
            for (int s = 0; s < LATE_WIN; s++) mbar_init(bars + B_PACE + s * 8, 1);
            mbar_init(bars + B_DOWN, 2);
#pragma unroll
            for (int r = 0; r < 6; r++) mbar_init(bars + B_WM + r * 8, 1);
            mbar_init(bars + B_FREE, 2);
            asm volatile("fence.mbarrier_init.release.cluster;" ::: "memory");
            fence_async_smem();
#pragma unroll
            for (int i = 0; i < START_WIN; i++) start_box(i);
            TS(0);
        }
    } else {
        epoch_raw = ld_poll1(&g_s.epoch[0]);
        if (warp >= 5) {
            c2pk = *reinterpret_cast<const uint32_t*>(c_in + 2 * at);
            x2pk = *reinterpret_cast<const uint32_t*>(x_in + 2 * at);
            if (at < 32) {
                if (b < N_MOD_CTA) st_pub1(&g_s.mod[b * 32 + at], 0u);
                if (b < N_Q_CTA) st_pub1(&g_s.q[b * 32 + at], 0u);
            }
        } else {
            const int hq = tid >> 6, d = (tid & 63) * 2;
            st_pub2(&g_s.po[0][hq * 4 + (d >> 5)][b][d & 31], 0u, 0u);
            if ((d & 31) < 8) st_pub2(&g_s.po[0][hq * 4 + (d >> 5)][b][32 + (d & 31)], 0u, 0u);
        }
    }
    __syncthreads();

    if (warp == 4) {
        if (lane == 0) {
            volatile int* s_tile = reinterpret_cast<volatile int*>(smem + SM_BAR + B_TILE);
            const uint64_t pol = policy_evict_first();
            constexpr int NSTAT = (NSLOT + 1) / 2;
            int t, tn;
            if (NSLOT & 1) { t = (NSTAT - 1) * G + b; tn = (int)atomicAdd(&g_s.ctr[0], 1u) + NSTAT * G; }
            else           { t = (int)atomicAdd(&g_s.ctr[0], 1u) + NSTAT * G; tn = 0; }
#pragma unroll
            for (int i = START_WIN; i < NSTART; i++) { start_wait(i - START_WIN); start_box(i); }
            TS(23);
            tma3d_prefetch((NSLOT & 1) ? &tmV : &tmK, t * TILE, pol);
            int s = 0;
            uint32_t ph = 0;
            bool skipK = (NSLOT & 1);
            while (true) {
                if (!skipK) {
                    tn = (int)atomicAdd(&g_s.ctr[0], 1u) + NSTAT * G;
                    mbar_wait(bars + B_EMPTY + s * 8, ph);
                    if (t >= NT) {
                        if (tn < t) __trap();
                        s_tile[s] = -1; mbar_arrive(bars + B_FULL + s * 8);
                        break;
                    }
                    s_tile[s] = t / TPH;
                    mbar_expect_tx(bars + B_FULL + s * 8, SLOT_BYTES);
                    tma3d(sb + SM_RING + s * SLOT_BYTES, &tmK, t * TILE, bars + B_FULL + s * 8, pol);
                    if (++s == NSLOT) { s = 0; ph ^= 1; }
                }
                skipK = false;
                mbar_wait(bars + B_EMPTY + s * 8, ph);
                mbar_expect_tx(bars + B_FULL + s * 8, SLOT_BYTES);
                tma3d(sb + SM_RING + s * SLOT_BYTES, &tmV, t * TILE, bars + B_FULL + s * 8, pol);
                if (++s == NSLOT) { s = 0; ph ^= 1; }
                t = tn;
            }
            TS(1);
            if (b < N_FFN_CTA) {
                mbar_wait(bars + B_FREE, 0);
                constexpr int UB = 9;
                constexpr int NBOX = UB + 9 - DE_GROUPS;
                int w = 0;
                uint32_t wp = 0;
#pragma unroll 1
                for (int i = 0; i < NBOX + LATE_WIN; i++) {
                    const uint32_t pb = bars + B_PACE + w * 8;
                    if (i >= LATE_WIN) {
                        mbar_wait(pb, wp ^ 1);
                        if (i - LATE_WIN == UB - 1) mbar_arrive(bars + B_U);
                    }
                    if (i < NBOX) {
                        mbar_expect_tx(pb, SM_DGRP);
                        if (i < UB) tma2d(sb + SM_U + i * SM_DGRP, &tmU, b * FCOLS, i * 64, pb);
                        else tma2d(sb + SM_D + (i - UB + DE_GROUPS) * SM_DGRP, &tmD, (i - UB + DE_GROUPS) * 64, b * FCOLS, pb);
                    }
                    if (++w == LATE_WIN) { w = 0; wp ^= 1; }
                }
                mbar_arrive(bars + B_DOWN);
            }
        }
        return;
    }

    const uint32_t tag = epoch_raw + 1u;

    if (warp < 4) {
        const int g = lane >> 2, t4 = lane & 3, mi = lane >> 3;
        const volatile int* s_tile = reinterpret_cast<const volatile int*>(smem + SM_BAR + B_TILE);
        uint32_t offK[2], offV[2];
        {
            const int keyK = warp * 16 + (lane & 7) + ((lane >> 3) & 1) * 8, hiK = lane >> 4;
            const int keyV = warp * 16 + (lane & 7) + (lane >> 4) * 8, hiV = (lane >> 3) & 1;
#pragma unroll
            for (int h = 0; h < 2; h++) {
                offK[h] = keyK * 256 + h * 128 + ((hiK ^ ((keyK * 2 + h) & 7)) << 4);
                offV[h] = keyV * 256 + h * 128 + ((hiV ^ ((keyV * 2 + h) & 7)) << 4);
            }
        }
        float acc[8][4];
#pragma unroll
        for (int i = 0; i < 8; i++) { acc[i][0] = acc[i][1] = acc[i][2] = acc[i][3] = 0.f; }
        uint32_t mrun = M_INIT;
        float l0 = 0.f, l1 = 0.f;
        uint32_t qb[8][2];
        int cur = 0;
        int fpar = 0;
        const int jobhead = (b < N_JOB_CTA) ? (b >> 3) : -1;

        auto load_q = [&](int h) {
            const uint32_t* q32 = reinterpret_cast<const uint32_t*>(smem + SM_Q) + (2 * h + (g & 1)) * 64 + t4;
#pragma unroll
            for (int ks = 0; ks < 8; ks++) { qb[ks][0] = q32[ks * 8]; qb[ks][1] = q32[ks * 8 + 4]; }
        };
        auto flush = [&](int h) {
            float* fb = reinterpret_cast<float*>(smem + SM_FB) + (fpar * 4 + warp) * 256;
            float* fml = reinterpret_cast<float*>(smem + SM_FML) + fpar * 16;
            float la = l0, lb = l1;
#pragma unroll
            for (int o = 4; o < 32; o <<= 1) { la += __shfl_xor_sync(0xffffffffu, la, o); lb += __shfl_xor_sync(0xffffffffu, lb, o); }
#pragma unroll
            for (int i = 0; i < 8; i++) {
                if ((i >> 1) == t4) {
                    fb[16 * i + g] = acc[i][0];           fb[128 + 16 * i + g] = acc[i][1];
                    fb[16 * i + g + 8] = acc[i][2];       fb[128 + 16 * i + g + 8] = acc[i][3];
                }
            }
            if (lane == 0) {
                fml[warp * 4 + 0] = bf_lo(mrun); fml[warp * 4 + 1] = la;
                fml[warp * 4 + 2] = bf_hi(mrun); fml[warp * 4 + 3] = lb;
            }
            bar_sync(1, NCONS);
            if (tid == 0 && h == jobhead) mbar_arrive(bars + B_JOB);
            if (tid == 0) TS(32 + h);
            {
                const int hq = tid >> 6, d = (tid & 63) * 2;
                const float* f0 = reinterpret_cast<const float*>(smem + SM_FB) + fpar * 1024 + hq * 128 + d;
                float mw[4], M = -3.4e38f;
#pragma unroll
                for (int w = 0; w < 4; w++) { mw[w] = fml[w * 4 + hq * 2]; M = fmaxf(M, mw[w]); }
                float o0 = 0.f, o1 = 0.f, L = 0.f;
#pragma unroll
                for (int w = 0; w < 4; w++) {
                    const float sc = ex2((mw[w] - M) * LOG2E);
                    const float2 v = *reinterpret_cast<const float2*>(f0 + w * 256);
                    o0 = fmaf(sc, v.x, o0); o1 = fmaf(sc, v.y, o1);
                    L = fmaf(sc, fml[w * 4 + hq * 2 + 1], L);
                }
                uint32_t* prow = &g_s.po[h][hq * 4 + (d >> 5)][b][d & 31];
                st_pub2(prow, tagf(o0, tag), tagf(o1, tag));
                if ((d & 31) < 8) st_pub2(prow + 32, tagf(M, tag), tagf(L, tag));
                if (h + 1 < HKV) {
                    st_pub2(prow + 8 * MAXG * PROW, 0u, 0u);
                    if ((d & 31) < 8) st_pub2(prow + 8 * MAXG * PROW + 32, 0u, 0u);
                }
                if (h == HKV - 2) {
                    uint32_t* row = (b < N_FFN_CTA) ? g_s.y2[b] : (b >= 120 && b < N_JOB_CTA) ? g_s.y[HKV - 1][b - 120] : nullptr;
                    if (row) {
                        st_pub4(row + tid * 4, 0u);
                        if (tid < 16) st_pub4(row + 512 + tid * 4, 0u);
                    }
                }
            }
            fpar ^= 1;
#pragma unroll
            for (int i = 0; i < 8; i++) { acc[i][0] = acc[i][1] = acc[i][2] = acc[i][3] = 0.f; }
            mrun = M_INIT; l0 = 0.f; l1 = 0.f;
        };

        mbar_wait(bars + B_QRDY, 0);
        if (tid == 0) TS(2);
        load_q(0);
        int s = 0;
        uint32_t ph = 0;
        while (true) {
            mbar_wait(bars + B_FULL + s * 8, ph);
            const int h = s_tile[s];
            if (h < 0) break;
            if (h != cur) {
                for (; cur < h; cur++) flush(cur);
                mbar_wait(bars + B_QALL, 0);
                load_q(h);
            }
            const uint32_t kbase = sb + SM_RING + s * SLOT_BYTES;
            float sa[4] = {0.f, 0.f, 0.f, 0.f}, sc2[4] = {0.f, 0.f, 0.f, 0.f};
            {
                uint32_t a[8][4];
#pragma unroll
                for (int ks = 0; ks < 8; ks++) ldsm4(a[ks], (kbase + offK[ks >> 2]) ^ ((ks & 3) << 5));
#pragma unroll
                for (int ks = 0; ks < 8; ks += 2) {
                    mma16816(sa, a[ks][0], a[ks][1], a[ks][2], a[ks][3], qb[ks][0], qb[ks][1]);
                    mma16816(sc2, a[ks + 1][0], a[ks + 1][1], a[ks + 1][2], a[ks + 1][3], qb[ks + 1][0], qb[ks + 1][1]);
                }
            }
            __syncwarp();
            if (lane == 0) mbar_arrive(bars + B_EMPTY + s * 8);
            if (++s == NSLOT) { s = 0; ph ^= 1; }
            uint32_t s01 = pack_bf16(sa[0] + sc2[0], sa[1] + sc2[1]);
            uint32_t s23 = pack_bf16(sa[2] + sc2[2], sa[3] + sc2[3]);
            s01 = pack_bf16(bf_lo(s01) * QK_SCALE, bf_hi(s01) * QK_SCALE);
            s23 = pack_bf16(bf_lo(s23) * QK_SCALE, bf_hi(s23) * QK_SCALE);
            uint32_t mx = max_bf16x2(s01, s23);
            mx = max_bf16x2(mx, __shfl_xor_sync(0xffffffffu, mx, 4));
            mx = max_bf16x2(mx, __shfl_xor_sync(0xffffffffu, mx, 8));
            mx = max_bf16x2(mx, __shfl_xor_sync(0xffffffffu, mx, 16));
            const uint32_t mnew = max_bf16x2(mrun, mx);
            if (mnew != mrun) {
                const float a0 = ex2((bf_lo(mrun) - bf_lo(mnew)) * LOG2E);
                const float a1 = ex2((bf_hi(mrun) - bf_hi(mnew)) * LOG2E);
                l0 *= a0; l1 *= a1;
#pragma unroll
                for (int i = 0; i < 8; i++) { acc[i][0] *= a0; acc[i][1] *= a1; acc[i][2] *= a0; acc[i][3] *= a1; }
                mrun = mnew;
            }
            const float m0 = bf_lo(mrun), m1 = bf_hi(mrun);
            const float p0 = ex2((bf_lo(s01) - m0) * LOG2E), p1 = ex2((bf_hi(s01) - m1) * LOG2E);
            const float p2 = ex2((bf_lo(s23) - m0) * LOG2E), p3 = ex2((bf_hi(s23) - m1) * LOG2E);
            l0 += p0 + p2; l1 += p1 + p3;
            const uint32_t pb0 = movmatrix_t(pack_bf16(p0, p1));
            const uint32_t pb1 = movmatrix_t(pack_bf16(p2, p3));
            mbar_wait(bars + B_FULL + s * 8, ph);
            {
                const uint32_t vbase = sb + SM_RING + s * SLOT_BYTES;
                uint32_t v[8][4];
#pragma unroll
                for (int i = 0; i < 8; i++) ldsm4t(v[i], (vbase + offV[i >> 2]) ^ ((i & 3) << 5));
#pragma unroll
                for (int i = 0; i < 8; i++) mma16816(acc[i], v[i][0], v[i][1], v[i][2], v[i][3], pb0, pb1);
            }
            __syncwarp();
            if (lane == 0) mbar_arrive(bars + B_EMPTY + s * 8);
            if (++s == NSLOT) { s = 0; ph ^= 1; }
        }
        if (tid == 0) TS(3);
        for (; cur < HKV; cur++) flush(cur);
        if (tid == 0) TS(4);
        if (tid == 0) mbar_arrive(bars + B_FREE);
        if (b >= N_FFN_CTA) return;
        {
            uint32_t da[9][10];
            mbar_wait(bars + B_DOWN, 0);
#pragma unroll
            for (int i = 0; i < 9; i++) {
                const int mt = warp * 9 + i;
                const int c = 2 * (mt & 3) + (mi & 1);
                const uint32_t base = sb + SM_D + (mt >> 2) * SM_DGRP;
                const int r0 = (lane & 7) + (mi >> 1) * 8, r2 = 32 + (lane & 7);
                uint32_t f[4];
                ldsm4t(f, base + r0 * 128 + ((c ^ (r0 & 7)) << 4));
                da[i][0] = f[0]; da[i][1] = f[1]; da[i][2] = f[2]; da[i][3] = f[3];
                ldsm4t(f, base + (r0 + 16) * 128 + ((c ^ (r0 & 7)) << 4));
                da[i][4] = f[0]; da[i][5] = f[1]; da[i][6] = f[2]; da[i][7] = f[3];
                ldsm2t(da[i][8], da[i][9], base + r2 * 128 + ((c ^ (r2 & 7)) << 4));
            }
            if (tid == 0) TS(19);
            bar_sync(3, NCONS + 64);
            const uint32_t* acts = reinterpret_cast<const uint32_t*>(smem + X_ACT);
            const uint32_t b00 = acts[t4], b01 = acts[4 + t4], b10 = acts[8 + t4], b11 = acts[12 + t4], b20 = acts[16 + t4];
            float y[9][4];
#pragma unroll
            for (int i = 0; i < 9; i++) {
                y[i][0] = y[i][1] = y[i][2] = y[i][3] = 0.f;
                mma16816(y[i], da[i][0], da[i][1], da[i][2], da[i][3], b00, b01);
            }
#pragma unroll
            for (int i = 0; i < 9; i++) mma16816(y[i], da[i][4], da[i][5], da[i][6], da[i][7], b10, b11);
#pragma unroll
            for (int i = 0; i < 9; i++) mma1688(y[i], da[i][8], da[i][9], b20);
            uint32_t* row = g_s.y2[b] + warp * 144 + g;
#pragma unroll
            for (int q = 0; q < 3; q++) {
                float r0 = y[4 * q][0], r1 = y[4 * q][2];
#pragma unroll
                for (int j = 1; j < 4; j++) if (4 * q + j < 9 && t4 == j) { r0 = y[4 * q + j][0]; r1 = y[4 * q + j][2]; }
                if (4 * q + t4 < 9) {
                    st_pub1(row + (4 * q + t4) * 16, tagf(r0, tag));
                    st_pub1(row + (4 * q + t4) * 16 + 8, tagf(r1, tag));
                }
            }
            if (tid == 0) TS(16);
        }
        return;
    }

    const int wa = at >> 5;
    auto load_wo = [&]() {
        fence_async_smem();
        mbar_expect_tx(bars + B_WO, 9 * SM_OGRP);
#pragma unroll
        for (int j = 0; j < 9; j++) tma2d(sb + SM_D + j * SM_OGRP, &tmO, j * 64, b * 32, bars + B_WO);
    };
    if (at == 0) TS(5);
    const float x0 = bf_lo(x2pk), x1 = bf_hi(x2pk);
    float mean1, rsd1;
    ln_stats(x0, x1, reinterpret_cast<float*>(smem + X_ST1), at, mean1, rsd1);
    {
        uint32_t fa[8][4];
        float* red0 = reinterpret_cast<float*>(smem + X_RED0);
        float* red1 = reinterpret_cast<float*>(smem + X_RED1);
        if (b < N_MOD_CTA) {
            const uint32_t cpk = pack_bf16(silu_f(bf_lo(c2pk)), silu_f(bf_hi(c2pk)));
            mbar_wait(bars + B_WM + (wa / 3) * 8, 0);
            if (at == 0) TS(20);
            load_frag32(fa, sb + SM_U, wa, lane);
            gemv32(fa, cpk, red0, wa, lane);
            bar_sync(2, NAUX);
            if (at < 32) {
                const float sum = sum9(red0 + at, 32);
                st_pub1(&g_s.mod[b * 32 + at], __float_as_uint(bfr(sum)) | tag);
            }
        }
        if (at == 0) TS(6);
        if (b < N_Q_CTA) {
            mbar_wait(bars + B_WQ + (wa / 3) * 8, 0);
            if (at == 0) TS(21);
            load_frag32(fa, sb + SM_D, wa, lane);
            uint2 sa2, ca2;
            unsigned it = 0;
            do {
                sa2 = ld_poll2(&g_s.mod[2 * at]);
                ca2 = ld_poll2(&g_s.mod[D_MODEL + 2 * at]);
                if (++it > SPIN_MAX) __trap();
            } while (bad2(sa2, tag) | bad2(ca2, tag));
            const uint32_t hpk = modulate2(x0, x1, mean1, rsd1, ca2, sa2);
            if (at == 0) TS(7);
            gemv32(fa, hpk, red1, wa, lane);
            bar_sync(2, NAUX);
            if (at < 32) {
                const float sum = sum9(red1 + at, 32);
                st_pub1(&g_s.q[b * 32 + at], __float_as_uint(bfr(sum)) | tag);
            }
        } else {
            const long long t0 = clock64();
            while (clock64() - t0 < 5000) __nanosleep(200);
        }
    }
    {
        uint2* q_s = reinterpret_cast<uint2*>(smem + SM_Q);
        if (wa < 2) {
            uint4 v0;
            unsigned it = 0;
            do { v0 = ld_poll4(&g_s.q[at * 4]); if (++it > SPIN_MAX) __trap(); } while (bad4(v0, tag));
            q_s[at] = make_uint2((v0.x >> 16) | (v0.y & 0xffff0000u), (v0.z >> 16) | (v0.w & 0xffff0000u));
            __syncwarp();
            if (lane == 0) mbar_arrive(bars + B_QRDY);
        }
        if (at == 0) TS(12);
        if (at == 0 && b < N_JOB_CTA) load_wo();
        uint4 v[4];
        unsigned it = 0;
        uint32_t pend = (64 + at + 3 * NAUX < 1024) ? 15u : 7u;
        do {
#pragma unroll
            for (int r = 0; r < 4; r++) if (pend & (1u << r)) v[r] = ld_poll4(&g_s.q[(64 + at + r * NAUX) * 4]);
#pragma unroll
            for (int r = 0; r < 4; r++) if ((pend & (1u << r)) && !bad4(v[r], tag)) pend &= ~(1u << r);
            if (++it > SPIN_MAX) __trap();
            if (pend) __nanosleep(200);
        } while (pend);
#pragma unroll
        for (int r = 0; r < 4; r++) {
            const int idx = 64 + at + r * NAUX;
            if (idx < 1024) q_s[idx] = make_uint2((v[r].x >> 16) | (v[r].y & 0xffff0000u), (v[r].z >> 16) | (v[r].w & 0xffff0000u));
        }
        __syncwarp();
        if (lane == 0) mbar_arrive(bars + B_QALL);
    }
    if (at == 0) TS(8);
    if (b >= N_JOB_CTA) return;
    const int g = lane >> 2, t4 = lane & 3, mi = lane >> 3;
    {
        const int h = b >> 3, sl = b & 7;
        float* jred = reinterpret_cast<float*>(smem + X_RED0);
        float* jml = reinterpret_cast<float*>(smem + X_JML);
        uint32_t oa[8][4];
        mbar_wait_long(bars + B_WO, 0);
#pragma unroll
        for (int mt = 0; mt < 4; mt++) {
#pragma unroll
            for (int ks = 0; ks < 2; ks++) {
                const int r = ks * 16 + (lane & 7) + (mi >> 1) * 8, c = 2 * mt + (mi & 1);
                ldsm4t(oa[mt * 2 + ks], sb + SM_D + wa * SM_OGRP + r * 128 + ((c ^ (r & 7)) << 4));
            }
        }
        if (b < N_FFN_CTA) {
            bar_sync(2, NAUX);
            if (at == 0) {
                fence_async_smem();
                mbar_expect_tx(bars + B_DOWN, DE_GROUPS * SM_DGRP);
#pragma unroll
                for (int j = 0; j < DE_GROUPS; j++) tma2d(sb + SM_D + j * SM_DGRP, &tmD, j * 64, b * FCOLS, bars + B_DOWN);
                mbar_arrive(bars + B_FREE);
            }
        }
        const int ycol = wa * 64 + t4 * 16 + g;
        uint32_t yp0 = 0, yp1 = 0;
        mbar_wait_long(bars + B_JOB, 0);
        if (h != HKV - 1) {
            const long long t0 = clock64();
            while (clock64() - t0 < JOB_DELAY_CLK) __nanosleep(400);
        }
        if (at == 0) TS(9);
        const int v = at & 7, bl = at >> 3;
        uint4 o4[4];
        uint2 ml[4];
        {
            const uint32_t* pO = &g_s.po[h][sl][0][0];
            const uint32_t* pY = &g_s.y[h > 0 ? h - 1 : 0][sl][ycol];
            uint32_t pend = 0;
#pragma unroll
            for (int r = 0; r < 4; r++) {
                o4[r] = make_uint4(0u, 0u, 0u, 0u); ml[r] = make_uint2(0u, 0x3f800000u);
                if (bl + 36 * r < G) pend |= 1u << r;
            }
            if (h > 0) pend |= 16u;
            unsigned it = 0;
            while (pend) {
#pragma unroll
                for (int r = 0; r < 4; r++) {
                    if (pend & (1u << r)) {
                        o4[r] = ld_poll4(pO + (bl + 36 * r) * PROW + v * 4);
                        ml[r] = ld_poll2(pO + (bl + 36 * r) * PROW + 32);
                    }
                }
                if (pend & 16u) {
                    yp0 = ld_poll1(pY);
                    yp1 = ld_poll1(pY + 8);
                }
#pragma unroll
                for (int r = 0; r < 4; r++)
                    if ((pend & (1u << r)) && !(bad4(o4[r], tag) | bad2(ml[r], tag))) pend &= ~(1u << r);
                if ((pend & 16u) && !(((yp0 ^ tag) | (yp1 ^ tag)) & 3u)) pend &= ~16u;
                if (++it > SPIN_MAX) __trap();
                if (pend && h != HKV - 1) __nanosleep(500);
            }
            __syncwarp();
        }
        if (at == 0) { TS(10); TC(58); }
        float Mw = -3.4e38f;
#pragma unroll
        for (int r = 0; r < 4; r++) if (bl + 36 * r < G) Mw = fmaxf(Mw, untag_bf(ml[r].x));
        Mw = fmaxf(Mw, __shfl_xor_sync(0xffffffffu, Mw, 8));
        Mw = fmaxf(Mw, __shfl_xor_sync(0xffffffffu, Mw, 16));
        float a4[4] = {0.f, 0.f, 0.f, 0.f}, ls = 0.f;
#pragma unroll
        for (int r = 0; r < 4; r++) {
            if (bl + 36 * r < G) {
                const float w = ex2((untag_bf(ml[r].x) - Mw) * LOG2E);
                a4[0] = fmaf(w, __uint_as_float(o4[r].x), a4[0]); a4[1] = fmaf(w, __uint_as_float(o4[r].y), a4[1]);
                a4[2] = fmaf(w, __uint_as_float(o4[r].z), a4[2]); a4[3] = fmaf(w, __uint_as_float(o4[r].w), a4[3]);
                ls = fmaf(w, __uint_as_float(ml[r].y), ls);
            }
        }
#pragma unroll
        for (int o = 8; o < 32; o <<= 1) {
#pragma unroll
            for (int j = 0; j < 4; j++) a4[j] += __shfl_xor_sync(0xffffffffu, a4[j], o);
            ls += __shfl_xor_sync(0xffffffffu, ls, o);
        }
        if (lane < 8) *reinterpret_cast<float4*>(&jred[wa * 32 + lane * 4]) = make_float4(a4[0], a4[1], a4[2], a4[3]);
        if (lane == 0) *reinterpret_cast<float2*>(&jml[wa * 2]) = make_float2(Mw, ls);
        if (at == 0) TC(59);
        bar_sync(2, NAUX);
        if (at == 0) TC(60);
        float2 mlw[9];
        float ow[9];
#pragma unroll
        for (int w = 0; w < 9; w++) { mlw[w] = *reinterpret_cast<const float2*>(&jml[2 * w]); ow[w] = jred[w * 32 + lane]; }
        const float M = fmaxf(fmaxf(fmaxf(fmaxf(mlw[0].x, mlw[1].x), fmaxf(mlw[2].x, mlw[3].x)),
                                    fmaxf(fmaxf(mlw[4].x, mlw[5].x), fmaxf(mlw[6].x, mlw[7].x))), mlw[8].x);
        float oe = 0.f, oo = 0.f, Le = 0.f, Lo = 0.f;
#pragma unroll
        for (int w = 0; w < 9; w++) {
            const float sc = ex2((mlw[w].x - M) * LOG2E);
            if (w & 1) { oo = fmaf(sc, ow[w], oo); Lo = fmaf(sc, mlw[w].y, Lo); }
            else       { oe = fmaf(sc, ow[w], oe); Le = fmaf(sc, mlw[w].y, Le); }
        }
        const float o = __fdividef(oe + oo, Le + Lo);
        if (at == 0) TC(61);
        const uint32_t opk = pack_bf16(o, __shfl_down_sync(0xffffffffu, o, 1));
        const uint32_t b00 = __shfl_sync(0xffffffffu, opk, 2 * t4), b01 = __shfl_sync(0xffffffffu, opk, 8 + 2 * t4);
        const uint32_t b10 = __shfl_sync(0xffffffffu, opk, 16 + 2 * t4), b11 = __shfl_sync(0xffffffffu, opk, 24 + 2 * t4);
        float y[4][4];
#pragma unroll
        for (int mt = 0; mt < 4; mt++) {
            y[mt][0] = y[mt][1] = y[mt][2] = y[mt][3] = 0.f;
            mma16816(y[mt], oa[2 * mt][0], oa[2 * mt][1], oa[2 * mt][2], oa[2 * mt][3], b00, b01);
        }
#pragma unroll
        for (int mt = 0; mt < 4; mt++)
            mma16816(y[mt], oa[2 * mt + 1][0], oa[2 * mt + 1][1], oa[2 * mt + 1][2], oa[2 * mt + 1][3], b10, b11);
        float r0 = y[0][0], r1 = y[0][2];
#pragma unroll
        for (int mt = 1; mt < 4; mt++) if (t4 == mt) { r0 = y[mt][0]; r1 = y[mt][2]; }
        if (h > 0) { r0 += __uint_as_float(yp0); r1 += __uint_as_float(yp1); }
        st_pub1(&g_s.y[h][sl][ycol], tagf(r0, tag));
        st_pub1(&g_s.y[h][sl][ycol + 8], tagf(r1, tag));
        if (at == 0) { TS(11); TC(62); }
    }
    if (b >= N_FFN_CTA) return;

    uint2 ga2, sb2, cb2;
    {
        unsigned it = 0;
        do {
            ga2 = ld_poll2(&g_s.mod[2 * D_MODEL + 2 * at]);
            sb2 = ld_poll2(&g_s.mod[3 * D_MODEL + 2 * at]);
            cb2 = ld_poll2(&g_s.mod[4 * D_MODEL + 2 * at]);
            if (++it > SPIN_MAX) __trap();
        } while (bad2(ga2, tag) | bad2(sb2, tag) | bad2(cb2, tag));
    }
    uint32_t gbv = 0;
    if (b < N_FIN_CTA && at < 8) {
        unsigned it = 0;
        do { gbv = ld_poll1(&g_s.mod[5 * D_MODEL + b * 8 + at]); if (++it > SPIN_MAX) __trap(); } while ((gbv ^ tag) & 3u);
    }
    uint32_t gf[10][4], uf[10][4];
    mbar_wait_long(bars + B_G, 0);
#pragma unroll
    for (int j = 0; j < 5; j++) {
        ldsm4t(gf[2 * j], sb + SM_G + (wa * 64 + lane) * 80 + j * 16);
        ldsm4t(gf[2 * j + 1], sb + SM_G + (wa * 64 + 32 + lane) * 80 + j * 16);
    }
    auto load_u = [&]() {
#pragma unroll
        for (int j = 0; j < 5; j++) {
            ldsm4t(uf[2 * j], sb + SM_U + (wa * 64 + lane) * 80 + j * 16);
            ldsm4t(uf[2 * j + 1], sb + SM_U + (wa * 64 + 32 + lane) * 80 + j * 16);
        }
    };
    float* x2s = reinterpret_cast<float*>(smem + T_X2);
    float2* tgu = reinterpret_cast<float2*>(smem + T_GU);
    float* tfin = reinterpret_cast<float*>(smem + X_FIN);
    bool have_u = false;
    uint32_t hpk;
    {
        uint2 v[8];
        unsigned it = 0;
        uint32_t pend = 255u;
        const uint32_t* pY = &g_s.y[HKV - 1][0][2 * at];
#pragma unroll
        for (int r = 0; r < 8; r++) v[r] = make_uint2(0u, 0u);
        while (__any_sync(0xffffffffu, pend != 0)) {
#pragma unroll
            for (int r = 0; r < 8; r++) if (pend & (1u << r)) v[r] = ld_poll2(pY + r * D_MODEL);
            if (!have_u && __all_sync(0xffffffffu, mbar_test(bars + B_U, 0))) {
                load_u(); have_u = true;
                if (at == 0) TS(22);
            }
#pragma unroll
            for (int r = 0; r < 8; r++) if ((pend & (1u << r)) && !bad2(v[r], tag)) pend &= ~(1u << r);
            if (++it > SPIN_MAX) __trap();
        }
        if (at == 0) { TS(13); TC(48); }
        const float s0 = ((__uint_as_float(v[0].x) + __uint_as_float(v[1].x)) + (__uint_as_float(v[2].x) + __uint_as_float(v[3].x))) +
                         ((__uint_as_float(v[4].x) + __uint_as_float(v[5].x)) + (__uint_as_float(v[6].x) + __uint_as_float(v[7].x)));
        const float s1 = ((__uint_as_float(v[0].y) + __uint_as_float(v[1].y)) + (__uint_as_float(v[2].y) + __uint_as_float(v[3].y))) +
                         ((__uint_as_float(v[4].y) + __uint_as_float(v[5].y)) + (__uint_as_float(v[6].y) + __uint_as_float(v[7].y)));
        const uint32_t apk = pack_bf16(s0, s1);
        const uint32_t gpk = pack_bf16(untag_bf(ga2.x) * bf_lo(apk), untag_bf(ga2.y) * bf_hi(apk));
        const uint32_t ypk = pack_bf16(x0 + bf_lo(gpk), x1 + bf_hi(gpk));
        const float y0 = bf_lo(ypk), y1 = bf_hi(ypk);
        *reinterpret_cast<float2*>(&x2s[2 * at]) = make_float2(y0, y1);
        float mean2, rsd2;
        if (at == 0) TC(49);
        ln_stats(y0, y1, reinterpret_cast<float*>(smem + X_ST2), at, mean2, rsd2);
        if (at == 0) TC(50);
        hpk = modulate2(y0, y1, mean2, rsd2, cb2, sb2);
    }
    if (!have_u) {
        mbar_wait(bars + B_U, 0);
        __syncwarp();
        load_u();
        if (at == 0) TS(22);
    }
    if (at == 0) { TS(14); TC(51); }
    {
        float y[5][4];
#pragma unroll
        for (int j = 0; j < 5; j++) y[j][0] = y[j][1] = y[j][2] = y[j][3] = 0.f;
#pragma unroll
        for (int ks = 0; ks < 4; ks++) {
            const uint32_t b0 = __shfl_sync(0xffffffffu, hpk, 8 * ks + t4);
            const uint32_t b1 = __shfl_sync(0xffffffffu, hpk, 8 * ks + 4 + t4);
            const int hf = ks >> 1, e = (ks & 1) * 2;
#pragma unroll
            for (int j = 0; j < 5; j++)
                mma16816(y[j], gf[2 * j + hf][e], uf[2 * j + hf][e], gf[2 * j + hf][e + 1], uf[2 * j + hf][e + 1], b0, b1);
        }
#pragma unroll
        for (int j = 0; j < 5; j++)
            if (t4 == (j & 3)) tgu[wa * FCOLS + j * 8 + g] = make_float2(y[j][0], y[j][2]);
    }
    if (at == 0) TC(52);
    bar_sync(2, NAUX);
    if (at == 0) TC(53);
    if (wa < 2) {
        if (at < FCOLS) {
            float2 p[9];
#pragma unroll
            for (int w = 0; w < 9; w++) p[w] = tgu[w * FCOLS + at];
            const float gs = (((p[0].x + p[1].x) + (p[2].x + p[3].x)) + ((p[4].x + p[5].x) + (p[6].x + p[7].x))) + p[8].x;
            const float us = (((p[0].y + p[1].y) + (p[2].y + p[3].y)) + ((p[4].y + p[5].y) + (p[6].y + p[7].y))) + p[8].y;
            const uint32_t gu = pack_bf16(gs, us);
            const float a = bfr(silu_f(bf_lo(gu))) * bf_hi(gu);
            reinterpret_cast<__nv_bfloat16*>(smem + X_ACT)[at] = __float2bfloat16_rn(a);
        }
        bar_arrive(3, NCONS + 64);
        if (at == 0) { TS(15); TC(54); }
    }
    if (b < N_FIN_CTA) {
        float a4[4] = {0.f, 0.f, 0.f, 0.f};
        if (at < 2 * N_FFN_CTA) {
            const uint32_t* pF = &g_s.y2[at >> 1][b * 8 + (at & 1) * 4];
            uint4 v;
            unsigned it = 0;
            do { v = ld_poll4(pF); if (++it > SPIN_MAX) __trap(); } while (bad4(v, tag));
            a4[0] = __uint_as_float(v.x); a4[1] = __uint_as_float(v.y); a4[2] = __uint_as_float(v.z); a4[3] = __uint_as_float(v.w);
        }
        __syncwarp();
        if (at == 0) { TS(18); TC(55); }
        const bool u1 = lane & 2, u2 = lane & 4;
        float k0 = (u1 ? a4[2] : a4[0]) + __shfl_xor_sync(0xffffffffu, u1 ? a4[0] : a4[2], 2);
        float k1 = (u1 ? a4[3] : a4[1]) + __shfl_xor_sync(0xffffffffu, u1 ? a4[1] : a4[3], 2);
        float k = (u2 ? k1 : k0) + __shfl_xor_sync(0xffffffffu, u2 ? k0 : k1, 4);
        k += __shfl_xor_sync(0xffffffffu, k, 8);
        k += __shfl_xor_sync(0xffffffffu, k, 16);
        if (lane < 8) tfin[wa * 8 + (lane & 1) * 4 + (lane & 2) + ((lane >> 2) & 1)] = k;
        if (at == 0) TC(56);
        bar_sync(2, NAUX);
        if (at < 8) {
            float v[8];
#pragma unroll
            for (int w = 0; w < 8; w++) v[w] = tfin[w * 8 + at];
            const float sum = ((v[0] + v[1]) + (v[2] + v[3])) + ((v[4] + v[5]) + (v[6] + v[7]));
            const float r = x2s[b * 8 + at] + bfr(untag_bf(gbv) * bfr(sum));
            out[b * 8 + at] = __float2bfloat16_rn(r);
        }
        if (at == 0) { TS(17); TC(57); }
    }
    if (b == 0 && at == 0) {
        g_s.ctr[0] = 0u;
        g_s.epoch[0] = (epoch_raw >= 2u) ? 0u : epoch_raw + 1u;
    }
}

typedef CUresult (*EncodeFn)(CUtensorMap*, CUtensorMapDataType, cuuint32_t, void*, const cuuint64_t*, const cuuint64_t*,
                             const cuuint32_t*, const cuuint32_t*, CUtensorMapInterleave, CUtensorMapSwizzle,
                             CUtensorMapL2promotion, CUtensorMapFloatOOBfill);

void make_2d(EncodeFn enc, CUtensorMap* m, void* base, uint64_t cols, uint64_t rows, uint32_t bcols, uint32_t brows,
             CUtensorMapSwizzle sw, CUtensorMapL2promotion pr) {
    cuuint64_t gd[2] = {cols, rows};
    cuuint64_t gs[1] = {cols * 2};
    cuuint32_t bx[2] = {bcols, brows};
    cuuint32_t es[2] = {1, 1};
    enc(m, CU_TENSOR_MAP_DATA_TYPE_BFLOAT16, 2, base, gd, gs, bx, es, CU_TENSOR_MAP_INTERLEAVE_NONE, sw, pr,
        CU_TENSOR_MAP_FLOAT_OOB_FILL_NONE);
}

}

extern "C" void kernel_launch(void* const* d_in, const int* in_sizes, int n_in, void* d_out, int out_size) {
    (void)in_sizes; (void)n_in; (void)out_size;
    static EncodeFn enc = nullptr;
    static int nsm = 0;
    if (!enc) {
        void* fn = nullptr;
        cudaDriverEntryPointQueryResult qr;
        cudaGetDriverEntryPoint("cuTensorMapEncodeTiled", &fn, cudaEnableDefault, &qr);
        enc = (EncodeFn)fn;
        int dev = 0;
        cudaGetDevice(&dev);
        cudaDeviceGetAttribute(&nsm, cudaDevAttrMultiProcessorCount, dev);
        cudaFuncSetAttribute(fused_kernel, cudaFuncAttributeMaxDynamicSharedMemorySize, SM_TOTAL);
    }
    if (!enc) return;

    CUtensorMap tmK, tmV, tmG, tmU, tmM, tmQ, tmO, tmD;
    {
        cuuint64_t gd[3] = {64, 2, (cuuint64_t)HKV * SK};
        cuuint64_t gs[2] = {128, 256};
        cuuint32_t bx[3] = {64, 2, TILE};
        cuuint32_t es[3] = {1, 1, 1};
        enc(&tmK, CU_TENSOR_MAP_DATA_TYPE_BFLOAT16, 3, d_in[1], gd, gs, bx, es, CU_TENSOR_MAP_INTERLEAVE_NONE,
            CU_TENSOR_MAP_SWIZZLE_128B, CU_TENSOR_MAP_L2_PROMOTION_NONE, CU_TENSOR_MAP_FLOAT_OOB_FILL_NONE);
        enc(&tmV, CU_TENSOR_MAP_DATA_TYPE_BFLOAT16, 3, d_in[2], gd, gs, bx, es, CU_TENSOR_MAP_INTERLEAVE_NONE,
            CU_TENSOR_MAP_SWIZZLE_128B, CU_TENSOR_MAP_L2_PROMOTION_NONE, CU_TENSOR_MAP_FLOAT_OOB_FILL_NONE);
    }
    make_2d(enc, &tmG, d_in[6], FF, D_MODEL, FCOLS, 192, CU_TENSOR_MAP_SWIZZLE_NONE, CU_TENSOR_MAP_L2_PROMOTION_L2_256B);
    make_2d(enc, &tmU, d_in[7], FF, D_MODEL, FCOLS, 64, CU_TENSOR_MAP_SWIZZLE_NONE, CU_TENSOR_MAP_L2_PROMOTION_L2_256B);
    make_2d(enc, &tmM, d_in[10], 6 * D_MODEL, D_MODEL, 32, 192, CU_TENSOR_MAP_SWIZZLE_64B, CU_TENSOR_MAP_L2_PROMOTION_L2_128B);
    make_2d(enc, &tmQ, d_in[3], 4096, D_MODEL, 32, 192, CU_TENSOR_MAP_SWIZZLE_64B, CU_TENSOR_MAP_L2_PROMOTION_L2_128B);
    make_2d(enc, &tmO, d_in[4], D_MODEL, 4096, 64, 32, CU_TENSOR_MAP_SWIZZLE_128B, CU_TENSOR_MAP_L2_PROMOTION_NONE);
    make_2d(enc, &tmD, d_in[8], D_MODEL, FF, 64, FCOLS, CU_TENSOR_MAP_SWIZZLE_128B, CU_TENSOR_MAP_L2_PROMOTION_NONE);

    int grid = nsm < MAXG ? nsm : MAXG;
    if (grid < N_JOB_CTA) return;
    fused_kernel<<<grid, NTHREADS, SM_TOTAL, cudaStreamPerThread>>>(
        tmK, tmV, tmG, tmU, tmM, tmQ, tmO, tmD, (const __nv_bfloat16*)d_in[0], (const __nv_bfloat16*)d_in[9],
        (__nv_bfloat16*)d_out);
}
```

```cpp
#include <cuda_runtime.h>
#include <cuda_bf16.h>
#include <cuda.h>
#include <stdint.h>

namespace {

constexpr int D_MODEL = 576;
constexpr int HKV = 16;
constexpr int SK = 65536;
constexpr int FF = 4608;
constexpr int TILE = 64;
constexpr int TPH = SK / TILE;
constexpr int NT = HKV * TPH;
#define EXP_NSLOT 3
constexpr int NSLOT = EXP_NSLOT;
constexpr int RING_SLOTS = 4;
constexpr int SLOT_BYTES = TILE * 256;
constexpr int MAXG = 144;
constexpr int N_MOD_CTA = 108;
constexpr int N_Q_CTA = 128;
constexpr int N_JOB_CTA = 128;
constexpr int N_FFN_CTA = 116;
constexpr int N_FIN_CTA = 72;
constexpr int FCOLS = 40;

#define JOB_DELAY_CLK 8000
#define START_WIN 3
#define Y_DELAY_CLK 4000
#define F_DELAY_CLK 600
#define Q_DELAY_CLK 4000
#define LATE_WIN 4

constexpr int NCONS = 128;
constexpr int NAUX = 288;
constexpr int NTHREADS = NCONS + 32 + NAUX;

constexpr int SM_RING = 0;
constexpr int SM_G = SM_RING + RING_SLOTS * SLOT_BYTES;
constexpr int SM_GSZ = D_MODEL * FCOLS * 2;
constexpr int SM_U = SM_G + SM_GSZ;
constexpr int SM_D = SM_U + SM_GSZ;
constexpr int SM_DGRP = FCOLS * 128;
constexpr int SM_OGRP = 32 * 128;
constexpr int SM_Q = SM_D + 9 * SM_DGRP;
constexpr int SM_FB = SM_Q + 8192;
constexpr int SM_FML = SM_FB + 8192;
constexpr int SM_X = SM_FML + 128;
constexpr int SM_T = SM_X + 4096;
constexpr int SM_BAR = SM_T + 6144;
constexpr int SM_TOTAL = SM_BAR + 512;
static_assert(SM_U % 1024 == 0 && SM_D % 1024 == 0, "swizzled regions must be 1024-aligned");
static_assert(SM_TOTAL <= 232448, "smem");
constexpr int X_ST1 = SM_X;
constexpr int X_ST2 = SM_X + 128;
constexpr int X_RED0 = SM_X + 256;
constexpr int X_RED1 = X_RED0 + 1152;
constexpr int X_JML = X_RED1 + 1152;
constexpr int X_ACT = X_JML + 128;
constexpr int X_FIN = X_ACT + 128;
constexpr int T_GU = SM_T;
constexpr int T_X2 = SM_T + 3072;
static_assert(X_FIN + 384 <= SM_T, "aux scratch");

constexpr int B_FULL = 0;
constexpr int B_EMPTY = 32;
constexpr int B_QRDY = 64;
constexpr int B_QALL = 112;
constexpr int B_JOB = 72;
constexpr int B_WO = 80;
constexpr int B_G = 88;
constexpr int B_WM = 208;
constexpr int B_WQ = 232;
constexpr int B_FREE = 136;
constexpr int B_LATE = 256;
constexpr int B_TILE = 192;

constexpr unsigned SPIN_MAX = 1u << 21;

constexpr int PROW = 40;
struct Scratch {
    uint32_t mod[3456];
    uint32_t q[4096];
    uint32_t po[HKV][8][MAXG][PROW];
    uint32_t y[HKV][8][D_MODEL];
    uint32_t y2[N_FFN_CTA][D_MODEL];
    uint32_t ctr[32];
    uint32_t epoch[32];
};
__device__ __align__(128) Scratch g_s;

#define TS(i) do { } while (0)
#define TC(i) do { } while (0)

__device__ __forceinline__ uint32_t smem_u32(const void* p) { return (uint32_t)__cvta_generic_to_shared(p); }
__device__ __forceinline__ void mbar_init(uint32_t bar, uint32_t cnt) {
    asm volatile("mbarrier.init.shared::cta.b64 [%0], %1;" ::"r"(bar), "r"(cnt) : "memory");
}
__device__ __forceinline__ void mbar_expect_tx(uint32_t bar, uint32_t bytes) {
    asm volatile("mbarrier.arrive.expect_tx.shared::cta.b64 _, [%0], %1;" ::"r"(bar), "r"(bytes) : "memory");
}
__device__ __forceinline__ void mbar_arrive(uint32_t bar) {
    asm volatile("mbarrier.arrive.shared::cta.b64 _, [%0];" ::"r"(bar) : "memory");
}
__device__ __forceinline__ bool mbar_try(uint32_t bar, uint32_t parity) {
    uint32_t ok;
    asm volatile("{\n.reg .pred p;\nmbarrier.try_wait.parity.shared::cta.b64 p, [%1], %2;\nselp.u32 %0, 1, 0, p;\n}"
                 : "=r"(ok) : "r"(bar), "r"(parity) : "memory");
    return ok != 0;
}
__device__ __forceinline__ bool mbar_test(uint32_t bar, uint32_t parity) {
    uint32_t ok;
    asm volatile("{\n.reg .pred p;\nmbarrier.test_wait.parity.shared::cta.b64 p, [%1], %2;\nselp.u32 %0, 1, 0, p;\n}"
                 : "=r"(ok) : "r"(bar), "r"(parity) : "memory");
    return ok != 0;
}
__device__ __forceinline__ void mbar_wait(uint32_t bar, uint32_t parity) {
    if (mbar_try(bar, parity)) return;
    const long long t0 = clock64();
    while (!mbar_try(bar, parity)) {
        if (clock64() - t0 > (1ll << 31)) __trap();
    }
}
__device__ __forceinline__ void mbar_wait_long(uint32_t bar, uint32_t parity) {
    const long long t0 = clock64();
    while (true) {
        uint32_t ok;
        asm volatile("{\n.reg .pred p;\nmbarrier.try_wait.parity.shared::cta.b64 p, [%1], %2, %3;\nselp.u32 %0, 1, 0, p;\n}"
                     : "=r"(ok) : "r"(bar), "r"(parity), "r"(200000u) : "memory");
        if (ok) return;
        if (clock64() - t0 > (1ll << 31)) __trap();
    }
}
__device__ __forceinline__ void bar_sync(int id, int n) { asm volatile("bar.sync %0, %1;" ::"r"(id), "r"(n) : "memory"); }
__device__ __forceinline__ void bar_arrive(int id, int n) { asm volatile("bar.arrive %0, %1;" ::"r"(id), "r"(n) : "memory"); }
__device__ __forceinline__ void fence_async_smem() { asm volatile("fence.proxy.async.shared::cta;" ::: "memory"); }

__device__ __forceinline__ uint64_t policy_evict_first() {
    uint64_t p;
    asm volatile("createpolicy.fractional.L2::evict_first.b64 %0, 1.0;" : "=l"(p));
    return p;
}
__device__ __forceinline__ void tma3d(uint32_t dst, const CUtensorMap* m, int c2, uint32_t bar, uint64_t pol) {
    asm volatile("cp.async.bulk.tensor.3d.shared::cluster.global.mbarrier::complete_tx::bytes.L2::cache_hint [%0], [%1, {%3, %3, %4}], [%2], %5;"
                 ::"r"(dst), "l"(m), "r"(bar), "r"(0), "r"(c2), "l"(pol) : "memory");
}
__device__ __forceinline__ void tma3d_prefetch(const CUtensorMap* m, int c2, uint64_t pol) {
    asm volatile("cp.async.bulk.prefetch.tensor.3d.L2.global.tile.L2::cache_hint [%0, {%1, %1, %2}], %3;"
                 ::"l"(m), "r"(0), "r"(c2), "l"(pol) : "memory");
}
__device__ __forceinline__ void tma2d(uint32_t dst, const CUtensorMap* m, int c0, int c1, uint32_t bar) {
    asm volatile("cp.async.bulk.tensor.2d.shared::cluster.global.mbarrier::complete_tx::bytes [%0], [%1, {%3, %4}], [%2];"
                 ::"r"(dst), "l"(m), "r"(bar), "r"(c0), "r"(c1) : "memory");
}
__device__ __forceinline__ void ldsm4(uint32_t (&r)[4], uint32_t addr) {
    asm volatile("ldmatrix.sync.aligned.m8n8.x4.shared.b16 {%0,%1,%2,%3}, [%4];"
                 : "=r"(r[0]), "=r"(r[1]), "=r"(r[2]), "=r"(r[3]) : "r"(addr) : "memory");
}
__device__ __forceinline__ void ldsm4t(uint32_t (&r)[4], uint32_t addr) {
    asm volatile("ldmatrix.sync.aligned.m8n8.x4.trans.shared.b16 {%0,%1,%2,%3}, [%4];"
                 : "=r"(r[0]), "=r"(r[1]), "=r"(r[2]), "=r"(r[3]) : "r"(addr) : "memory");
}
__device__ __forceinline__ void ldsm2t(uint32_t& r0, uint32_t& r1, uint32_t addr) {
    asm volatile("ldmatrix.sync.aligned.m8n8.x2.trans.shared.b16 {%0,%1}, [%2];" : "=r"(r0), "=r"(r1) : "r"(addr) : "memory");
}
__device__ __forceinline__ void mma16816(float (&c)[4], uint32_t a0, uint32_t a1, uint32_t a2, uint32_t a3, uint32_t b0, uint32_t b1) {
    asm volatile("mma.sync.aligned.m16n8k16.row.col.f32.bf16.bf16.f32 {%0,%1,%2,%3}, {%4,%5,%6,%7}, {%8,%9}, {%0,%1,%2,%3};"
                 : "+f"(c[0]), "+f"(c[1]), "+f"(c[2]), "+f"(c[3])
                 : "r"(a0), "r"(a1), "r"(a2), "r"(a3), "r"(b0), "r"(b1));
}
__device__ __forceinline__ void mma1688(float (&c)[4], uint32_t a0, uint32_t a1, uint32_t b0) {
    asm volatile("mma.sync.aligned.m16n8k8.row.col.f32.bf16.bf16.f32 {%0,%1,%2,%3}, {%4,%5}, {%6}, {%0,%1,%2,%3};"
                 : "+f"(c[0]), "+f"(c[1]), "+f"(c[2]), "+f"(c[3])
                 : "r"(a0), "r"(a1), "r"(b0));
}
__device__ __forceinline__ uint32_t movmatrix_t(uint32_t a) {
    uint32_t d;
    asm volatile("movmatrix.sync.aligned.m8n8.trans.b16 %0, %1;" : "=r"(d) : "r"(a));
    return d;
}
__device__ __forceinline__ uint32_t pack_bf16(float lo, float hi) {
    uint32_t d;
    asm("cvt.rn.bf16x2.f32 %0, %1, %2;" : "=r"(d) : "f"(hi), "f"(lo));
    return d;
}
__device__ __forceinline__ float bf_lo(uint32_t v) { return __uint_as_float(v << 16); }
__device__ __forceinline__ float bf_hi(uint32_t v) { return __uint_as_float(v & 0xffff0000u); }
__device__ __forceinline__ float bfr(float x) { return bf_lo(pack_bf16(x, 0.f)); }
__device__ __forceinline__ uint32_t max_bf16x2(uint32_t a, uint32_t b) {
    uint32_t d;
    asm("max.bf16x2 %0, %1, %2;" : "=r"(d) : "r"(a), "r"(b));
    return d;
}
__device__ __forceinline__ float ex2(float x) {
    float y;
    asm("ex2.approx.ftz.f32 %0, %1;" : "=f"(y) : "f"(x));
    return y;
}
__device__ __forceinline__ float silu_f(float x) { return __fdividef(x, 1.0f + __expf(-x)); }

__device__ __forceinline__ uint4 ld_poll4(const uint32_t* p) {
    uint4 v;
    asm volatile("ld.relaxed.gpu.global.v4.u32 {%0,%1,%2,%3}, [%4];" : "=r"(v.x), "=r"(v.y), "=r"(v.z), "=r"(v.w) : "l"(p) : "memory");
    return v;
}
__device__ __forceinline__ uint2 ld_poll2(const uint32_t* p) {
    uint2 v;
    asm volatile("ld.relaxed.gpu.global.v2.u32 {%0,%1}, [%2];" : "=r"(v.x), "=r"(v.y) : "l"(p) : "memory");
    return v;
}
__device__ __forceinline__ uint32_t ld_poll1(const uint32_t* p) {
    uint32_t v;
    asm volatile("ld.relaxed.gpu.global.u32 %0, [%1];" : "=r"(v) : "l"(p) : "memory");
    return v;
}
__device__ __forceinline__ void st_pub1(uint32_t* p, uint32_t a) {
    asm volatile("st.relaxed.gpu.global.u32 [%0], %1;" ::"l"(p), "r"(a) : "memory");
}
__device__ __forceinline__ void st_pub2(uint32_t* p, uint32_t a, uint32_t b) {
    asm volatile("st.relaxed.gpu.global.v2.u32 [%0], {%1,%2};" ::"l"(p), "r"(a), "r"(b) : "memory");
}
__device__ __forceinline__ void st_pub4(uint32_t* p, uint32_t a) {
    asm volatile("st.relaxed.gpu.global.v4.u32 [%0], {%1,%1,%1,%1};" ::"l"(p), "r"(a) : "memory");
}
__device__ __forceinline__ uint32_t tagf(float v, uint32_t tag) { return (__float_as_uint(v) & ~3u) | tag; }
__device__ __forceinline__ uint32_t bad4(const uint4& v, uint32_t tag) { return ((v.x ^ tag) | (v.y ^ tag) | (v.z ^ tag) | (v.w ^ tag)) & 3u; }
__device__ __forceinline__ uint32_t bad2(const uint2& v, uint32_t tag) { return ((v.x ^ tag) | (v.y ^ tag)) & 3u; }
__device__ __forceinline__ float untag_bf(uint32_t v) { return __uint_as_float(v & 0xffff0000u); }

constexpr float LOG2E = 1.4426950408889634f;
constexpr float QK_SCALE = 0.08838834764831845f;
constexpr uint32_t M_INIT = 0xFF7FFF7Fu;

__device__ __forceinline__ void ln_stats(float x0, float x1, float* st, int at, float& mean_r, float& rsd) {
    const float piv = __shfl_sync(0xffffffffu, x0, 0);
    const float d0 = x0 - piv, d1 = x1 - piv;
    float s1 = d0 + d1, s2 = fmaf(d0, d0, d1 * d1);
#pragma unroll
    for (int o = 1; o < 32; o <<= 1) {
        s1 += __shfl_xor_sync(0xffffffffu, s1, o);
        s2 += __shfl_xor_sync(0xffffffffu, s2, o);
    }
    if ((at & 31) == 0)
        *reinterpret_cast<float2*>(&st[(at >> 5) * 2]) = make_float2(fmaf(s1, 1.0f / 64.0f, piv), fmaf(s1 * s1, -1.0f / 64.0f, s2));
    bar_sync(2, NAUX);
    float2 sw[9];
#pragma unroll
    for (int w = 0; w < 9; w++) sw[w] = *reinterpret_cast<const float2*>(&st[2 * w]);
    const float ms = (((sw[0].x + sw[1].x) + (sw[2].x + sw[3].x)) + ((sw[4].x + sw[5].x) + (sw[6].x + sw[7].x))) + sw[8].x;
    const float m2s = (((sw[0].y + sw[1].y) + (sw[2].y + sw[3].y)) + ((sw[4].y + sw[5].y) + (sw[6].y + sw[7].y))) + sw[8].y;
    const float mu = ms * (1.0f / 9.0f);
    float e[9];
#pragma unroll
    for (int w = 0; w < 9; w++) e[w] = sw[w].x - mu;
    const float dd = ((fmaf(e[0], e[0], e[1] * e[1]) + fmaf(e[2], e[2], e[3] * e[3])) +
                      (fmaf(e[4], e[4], e[5] * e[5]) + fmaf(e[6], e[6], e[7] * e[7]))) + e[8] * e[8];
    const float var = fmaxf(fmaf(64.f, dd, m2s), 0.f) * (1.0f / 576.0f);
    mean_r = bfr(mu);
    float sd;
    asm("sqrt.approx.f32 %0, %1;" : "=f"(sd) : "f"(bfr(bfr(var) + 1e-5f)));
    sd = bfr(sd);
    asm("rcp.approx.f32 %0, %1;" : "=f"(rsd) : "f"(sd));
}
__device__ __forceinline__ uint32_t modulate2(float x0, float x1, float mean_r, float rsd, uint2 scale, uint2 shift) {
    const uint32_t dpk = pack_bf16(x0 - mean_r, x1 - mean_r);
    const uint32_t npk = pack_bf16(bf_lo(dpk) * rsd, bf_hi(dpk) * rsd);
    const uint32_t cpk = pack_bf16(1.0f + untag_bf(scale.x), 1.0f + untag_bf(scale.y));
    const uint32_t mpk = pack_bf16(bf_lo(npk) * bf_lo(cpk), bf_hi(npk) * bf_hi(cpk));
    return pack_bf16(bf_lo(mpk) + untag_bf(shift.x), bf_hi(mpk) + untag_bf(shift.y));
}
__device__ __forceinline__ float sum9(const float* p, int stride) {
    float v[9];
#pragma unroll
    for (int w = 0; w < 9; w++) v[w] = p[w * stride];
    return (((v[0] + v[1]) + (v[2] + v[3])) + ((v[4] + v[5]) + (v[6] + v[7]))) + v[8];
}

__device__ __forceinline__ void load_frag32(uint32_t (&a)[8][4], uint32_t base, int wa, int lane) {
    const int mi = lane >> 3;
#pragma unroll
    for (int ks = 0; ks < 4; ks++) {
        const int r = wa * 64 + ks * 16 + (lane & 7) + (mi >> 1) * 8;
#pragma unroll
        for (int j = 0; j < 2; j++) {
            const int c = 2 * j + (mi & 1);
            ldsm4t(a[j * 4 + ks], base + r * 64 + ((c ^ ((r >> 1) & 3)) << 4));
        }
    }
}
__device__ __forceinline__ void gemv32(const uint32_t (&a)[8][4], uint32_t pk, float* red, int wa, int lane) {
    const int g = lane >> 2, t4 = lane & 3;
    float c0[4] = {0.f, 0.f, 0.f, 0.f}, c1[4] = {0.f, 0.f, 0.f, 0.f};
#pragma unroll
    for (int ks = 0; ks < 4; ks++) {
        const uint32_t b0 = __shfl_sync(0xffffffffu, pk, 8 * ks + t4);
        const uint32_t b1 = __shfl_sync(0xffffffffu, pk, 8 * ks + 4 + t4);
        mma16816(c0, a[ks][0], a[ks][1], a[ks][2], a[ks][3], b0, b1);
        mma16816(c1, a[4 + ks][0], a[4 + ks][1], a[4 + ks][2], a[4 + ks][3], b0, b1);
    }
    if (t4 == 0) { red[wa * 32 + g] = c0[0]; red[wa * 32 + 8 + g] = c0[2]; }
    if (t4 == 1) { red[wa * 32 + 16 + g] = c1[0]; red[wa * 32 + 24 + g] = c1[2]; }
}

__global__ void __launch_bounds__(NTHREADS, 1)
fused_kernel(const __grid_constant__ CUtensorMap tmK, const __grid_constant__ CUtensorMap tmV,
             const __grid_constant__ CUtensorMap tmG, const __grid_constant__ CUtensorMap tmU,
             const __grid_constant__ CUtensorMap tmM, const __grid_constant__ CUtensorMap tmQ,
             const __grid_constant__ CUtensorMap tmO, const __grid_constant__ CUtensorMap tmD,
             const __nv_bfloat16* __restrict__ x_in, const __nv_bfloat16* __restrict__ c_in,
             __nv_bfloat16* __restrict__ out)
{
    extern __shared__ __align__(1024) uint8_t smem[];
    const uint32_t sb = smem_u32(smem);
    const int tid = threadIdx.x, warp = tid >> 5, lane = tid & 31;
    const int b = blockIdx.x, G = gridDim.x;
    const uint32_t bars = sb + SM_BAR;
    const int at = tid - (NCONS + 32);

    if (tid == 0) TS(24);
    constexpr int NSTART = 6 + NSLOT + 3;
    auto start_box = [&](int i) {
        if (i < 3) {
            if (b < N_MOD_CTA) {
                mbar_expect_tx(bars + B_WM + i * 8, 192 * 64);
                tma2d(sb + SM_U + i * 192 * 64, &tmM, b * 32, i * 192, bars + B_WM + i * 8);
            }
        } else if (i < 6) {
            if (b < N_Q_CTA) {
                mbar_expect_tx(bars + B_WM + i * 8, 192 * 64);
                tma2d(sb + SM_D + (i - 3) * 192 * 64, &tmQ, b * 32, (i - 3) * 192, bars + B_WM + i * 8);
            }
        } else if (i < 6 + NSLOT) {
            const int k = i - 6, ti = (k >> 1) * G + b;
            if (!(k & 1)) reinterpret_cast<volatile int*>(smem + SM_BAR + B_TILE)[k] = ti / TPH;
            mbar_expect_tx(bars + B_FULL + k * 8, SLOT_BYTES);
            tma3d(sb + SM_RING + k * SLOT_BYTES, (k & 1) ? &tmV : &tmK, ti * TILE, bars + B_FULL + k * 8, policy_evict_first());
        } else if (b < N_FFN_CTA) {
            const int r = i - 6 - NSLOT;
            if (r == 0) mbar_expect_tx(bars + B_G, SM_GSZ);
            tma2d(sb + SM_G + r * 192 * 80, &tmG, b * FCOLS, r * 192, bars + B_G);
        }
    };
    auto start_wait = [&](int i) {
        if (i < 3) { if (b < N_MOD_CTA) mbar_wait(bars + B_WM + i * 8, 0); }
        else if (i < 6) { if (b < N_Q_CTA) mbar_wait(bars + B_WM + i * 8, 0); }
        else if (i < 6 + NSLOT) mbar_wait(bars + B_FULL + (i - 6) * 8, 0);
    };
    uint32_t x2pk = 0, c2pk = 0, epoch_raw = 0;
    if (warp == 4) {
        if (lane == 0) {
            if (sb & 1023u) __trap();
#pragma unroll
            for (int s = 0; s < NSLOT; s++) { mbar_init(bars + B_FULL + s * 8, 1); mbar_init(bars + B_EMPTY + s * 8, 4); }
            mbar_init(bars + B_QRDY, 2);
            mbar_init(bars + B_QALL, NAUX / 32);
            mbar_init(bars + B_JOB, 1);
            mbar_init(bars + B_WO, 1);
            mbar_init(bars + B_G, 1);
#pragma unroll
            for (int s = 0; s < 18; s++) mbar_init(bars + B_LATE + s * 8, 1);
#pragma unroll
            for (int r = 0; r < 6; r++) mbar_init(bars + B_WM + r * 8, 1);
            mbar_init(bars + B_FREE, 2);
            asm volatile("fence.mbarrier_init.release.cluster;" ::: "memory");
            fence_async_smem();
#pragma unroll
            for (int i = 0; i < START_WIN; i++) start_box(i);
            TS(0);
        }
    } else {
        epoch_raw = ld_poll1(&g_s.epoch[0]);
        if (warp >= 5) {
            c2pk = *reinterpret_cast<const uint32_t*>(c_in + 2 * at);
            x2pk = *reinterpret_cast<const uint32_t*>(x_in + 2 * at);
            if (at < 32) {
                if (b < N_MOD_CTA) st_pub1(&g_s.mod[b * 32 + at], 0u);
                if (b < N_Q_CTA) st_pub1(&g_s.q[b * 32 + at], 0u);
            }
        } else {
            const int hq = tid >> 6, d = (tid & 63) * 2;
            st_pub2(&g_s.po[0][hq * 4 + (d >> 5)][b][d & 31], 0u, 0u);
            if ((d & 31) < 8) st_pub2(&g_s.po[0][hq * 4 + (d >> 5)][b][32 + (d & 31)], 0u, 0u);
        }
    }
    __syncthreads();

    if (warp == 4) {
        if (lane == 0) {
            volatile int* s_tile = reinterpret_cast<volatile int*>(smem + SM_BAR + B_TILE);
            const uint64_t pol = policy_evict_first();
            constexpr int NSTAT = (NSLOT + 1) / 2;
            int t, tn;
            if (NSLOT & 1) { t = (NSTAT - 1) * G + b; tn = (int)atomicAdd(&g_s.ctr[0], 1u) + NSTAT * G; }
            else           { t = (int)atomicAdd(&g_s.ctr[0], 1u) + NSTAT * G; tn = 0; }
#pragma unroll
            for (int i = START_WIN; i < NSTART; i++) { start_wait(i - START_WIN); start_box(i); }
            TS(23);
            tma3d_prefetch((NSLOT & 1) ? &tmV : &tmK, t * TILE, pol);
            int s = 0;
            uint32_t ph = 0;
            bool skipK = (NSLOT & 1);
            while (true) {
                if (!skipK) {
                    tn = (int)atomicAdd(&g_s.ctr[0], 1u) + NSTAT * G;
                    mbar_wait(bars + B_EMPTY + s * 8, ph);
                    if (t >= NT) {
                        if (tn < t) __trap();
                        s_tile[s] = -1; mbar_arrive(bars + B_FULL + s * 8);
                        break;
                    }
                    s_tile[s] = t / TPH;
                    mbar_expect_tx(bars + B_FULL + s * 8, SLOT_BYTES);
                    tma3d(sb + SM_RING + s * SLOT_BYTES, &tmK, t * TILE, bars + B_FULL + s * 8, pol);
                    if (++s == NSLOT) { s = 0; ph ^= 1; }
                }
                skipK = false;
                mbar_wait(bars + B_EMPTY + s * 8, ph);
                mbar_expect_tx(bars + B_FULL + s * 8, SLOT_BYTES);
                tma3d(sb + SM_RING + s * SLOT_BYTES, &tmV, t * TILE, bars + B_FULL + s * 8, pol);
                if (++s == NSLOT) { s = 0; ph ^= 1; }
                t = tn;
            }
            TS(1);
            if (b < N_FFN_CTA) {
#pragma unroll
                for (int i = 0; i < 18; i++) mbar_expect_tx(bars + B_LATE + i * 8, SM_DGRP);
                mbar_wait(bars + B_FREE, 0);
#pragma unroll 1
                for (int i = 0; i < 9; i++) {
                    if (i >= LATE_WIN) mbar_wait(bars + B_LATE + (i - LATE_WIN) * 8, 0);
                    tma2d(sb + SM_U + i * SM_DGRP, &tmU, b * FCOLS, i * 64, bars + B_LATE + i * 8);
                }
#pragma unroll 1
                for (int i = 0; i < 9; i++) {
                    mbar_wait(bars + B_LATE + (9 + i - LATE_WIN) * 8, 0);
                    tma2d(sb + SM_D + i * SM_DGRP, &tmD, i * 64, b * FCOLS, bars + B_LATE + (9 + i) * 8);
                }
            }
        }
        return;
    }

    const uint32_t tag = epoch_raw + 1u;

    if (warp < 4) {
        const int g = lane >> 2, t4 = lane & 3, mi = lane >> 3;
        const volatile int* s_tile = reinterpret_cast<const volatile int*>(smem + SM_BAR + B_TILE);
        uint32_t offK[2], offV[2];
        {
            const int keyK = warp * 16 + (lane & 7) + ((lane >> 3) & 1) * 8, hiK = lane >> 4;
            const int keyV = warp * 16 + (lane & 7) + (lane >> 4) * 8, hiV = (lane >> 3) & 1;
#pragma unroll
            for (int h = 0; h < 2; h++) {
                offK[h] = keyK * 256 + h * 128 + ((hiK ^ ((keyK * 2 + h) & 7)) << 4);
                offV[h] = keyV * 256 + h * 128 + ((hiV ^ ((keyV * 2 + h) & 7)) << 4);
            }
        }
        float acc[8][4];
#pragma unroll
        for (int i = 0; i < 8; i++) { acc[i][0] = acc[i][1] = acc[i][2] = acc[i][3] = 0.f; }
        uint32_t mrun = M_INIT;
        float l0 = 0.f, l1 = 0.f;
        uint32_t qb[8][2];
        int cur = 0;
        int fpar = 0;
        const int jobhead = (b < N_JOB_CTA) ? (b >> 3) : -1;

        auto load_q = [&](int h) {
            const uint32_t* q32 = reinterpret_cast<const uint32_t*>(smem + SM_Q) + (2 * h + (g & 1)) * 64 + t4;
#pragma unroll
            for (int ks = 0; ks < 8; ks++) { qb[ks][0] = q32[ks * 8]; qb[ks][1] = q32[ks * 8 + 4]; }
        };
        auto flush = [&](int h) {
            float* fb = reinterpret_cast<float*>(smem + SM_FB) + (fpar * 4 + warp) * 256;
            float* fml = reinterpret_cast<float*>(smem + SM_FML) + fpar * 16;
            float la = l0, lb = l1;
#pragma unroll
            for (int o = 4; o < 32; o <<= 1) { la += __shfl_xor_sync(0xffffffffu, la, o); lb += __shfl_xor_sync(0xffffffffu, lb, o); }
#pragma unroll
            for (int i = 0; i < 8; i++) {
                if ((i >> 1) == t4) {
                    fb[16 * i + g] = acc[i][0];           fb[128 + 16 * i + g] = acc[i][1];
                    fb[16 * i + g + 8] = acc[i][2];       fb[128 + 16 * i + g + 8] = acc[i][3];
                }
            }
            if (lane == 0) {
                fml[warp * 4 + 0] = bf_lo(mrun); fml[warp * 4 + 1] = la;
                fml[warp * 4 + 2] = bf_hi(mrun); fml[warp * 4 + 3] = lb;
            }
            bar_sync(1, NCONS);
            if (tid == 0 && h == jobhead) mbar_arrive(bars + B_JOB);
            if (tid == 0) TS(32 + h);
            {
                const int hq = tid >> 6, d = (tid & 63) * 2;
                const float* f0 = reinterpret_cast<const float*>(smem + SM_FB) + fpar * 1024 + hq * 128 + d;
                float mw[4], M = -3.4e38f;
#pragma unroll
                for (int w = 0; w < 4; w++) { mw[w] = fml[w * 4 + hq * 2]; M = fmaxf(M, mw[w]); }
                float o0 = 0.f, o1 = 0.f, L = 0.f;
#pragma unroll
                for (int w = 0; w < 4; w++) {
                    const float sc = ex2((mw[w] - M) * LOG2E);
                    const float2 v = *reinterpret_cast<const float2*>(f0 + w * 256);
                    o0 = fmaf(sc, v.x, o0); o1 = fmaf(sc, v.y, o1);
                    L = fmaf(sc, fml[w * 4 + hq * 2 + 1], L);
                }
                uint32_t* prow = &g_s.po[h][hq * 4 + (d >> 5)][b][d & 31];
                st_pub2(prow, tagf(o0, tag), tagf(o1, tag));
                if ((d & 31) < 8) st_pub2(prow + 32, tagf(M, tag), tagf(L, tag));
                if (h + 1 < HKV) {
                    st_pub2(prow + 8 * MAXG * PROW, 0u, 0u);
                    if ((d & 31) < 8) st_pub2(prow + 8 * MAXG * PROW + 32, 0u, 0u);
                }
                if (h == HKV - 2) {
                    uint32_t* row = (b < N_FFN_CTA) ? g_s.y2[b] : (b >= 120 && b < N_JOB_CTA) ? g_s.y[HKV - 1][b - 120] : nullptr;
                    if (row) {
                        st_pub4(row + tid * 4, 0u);
                        if (tid < 16) st_pub4(row + 512 + tid * 4, 0u);
                    }
                }
            }
            fpar ^= 1;
#pragma unroll
            for (int i = 0; i < 8; i++) { acc[i][0] = acc[i][1] = acc[i][2] = acc[i][3] = 0.f; }
            mrun = M_INIT; l0 = 0.f; l1 = 0.f;
        };

        mbar_wait(bars + B_QRDY, 0);
        if (tid == 0) TS(2);
        load_q(0);
        int s = 0;
        uint32_t ph = 0;
        while (true) {
            mbar_wait(bars + B_FULL + s * 8, ph);
            const int h = s_tile[s];
            if (h < 0) break;
            if (h != cur) {
                for (; cur < h; cur++) flush(cur);
                mbar_wait(bars + B_QALL, 0);
                load_q(h);
            }
            const uint32_t kbase = sb + SM_RING + s * SLOT_BYTES;
            float sa[4] = {0.f, 0.f, 0.f, 0.f}, sc2[4] = {0.f, 0.f, 0.f, 0.f};
            {
                uint32_t a[8][4];
#pragma unroll
                for (int ks = 0; ks < 8; ks++) ldsm4(a[ks], (kbase + offK[ks >> 2]) ^ ((ks & 3) << 5));
#pragma unroll
                for (int ks = 0; ks < 8; ks += 2) {
                    mma16816(sa, a[ks][0], a[ks][1], a[ks][2], a[ks][3], qb[ks][0], qb[ks][1]);
                    mma16816(sc2, a[ks + 1][0], a[ks + 1][1], a[ks + 1][2], a[ks + 1][3], qb[ks + 1][0], qb[ks + 1][1]);
                }
            }
            __syncwarp();
            if (lane == 0) mbar_arrive(bars + B_EMPTY + s * 8);
            if (++s == NSLOT) { s = 0; ph ^= 1; }
            uint32_t s01 = pack_bf16(sa[0] + sc2[0], sa[1] + sc2[1]);
            uint32_t s23 = pack_bf16(sa[2] + sc2[2], sa[3] + sc2[3]);
            s01 = pack_bf16(bf_lo(s01) * QK_SCALE, bf_hi(s01) * QK_SCALE);
            s23 = pack_bf16(bf_lo(s23) * QK_SCALE, bf_hi(s23) * QK_SCALE);
            uint32_t mx = max_bf16x2(s01, s23);
            mx = max_bf16x2(mx, __shfl_xor_sync(0xffffffffu, mx, 4));
            mx = max_bf16x2(mx, __shfl_xor_sync(0xffffffffu, mx, 8));
            mx = max_bf16x2(mx, __shfl_xor_sync(0xffffffffu, mx, 16));
            const uint32_t mnew = max_bf16x2(mrun, mx);
            if (mnew != mrun) {
                const float a0 = ex2((bf_lo(mrun) - bf_lo(mnew)) * LOG2E);
                const float a1 = ex2((bf_hi(mrun) - bf_hi(mnew)) * LOG2E);
                l0 *= a0; l1 *= a1;
#pragma unroll
                for (int i = 0; i < 8; i++) { acc[i][0] *= a0; acc[i][1] *= a1; acc[i][2] *= a0; acc[i][3] *= a1; }
                mrun = mnew;
            }
            const float m0 = bf_lo(mrun), m1 = bf_hi(mrun);
            const float p0 = ex2((bf_lo(s01) - m0) * LOG2E), p1 = ex2((bf_hi(s01) - m1) * LOG2E);
            const float p2 = ex2((bf_lo(s23) - m0) * LOG2E), p3 = ex2((bf_hi(s23) - m1) * LOG2E);
            l0 += p0 + p2; l1 += p1 + p3;
            const uint32_t pb0 = movmatrix_t(pack_bf16(p0, p1));
            const uint32_t pb1 = movmatrix_t(pack_bf16(p2, p3));
            mbar_wait(bars + B_FULL + s * 8, ph);
            {
                const uint32_t vbase = sb + SM_RING + s * SLOT_BYTES;
                uint32_t v[8][4];
#pragma unroll
                for (int i = 0; i < 8; i++) ldsm4t(v[i], (vbase + offV[i >> 2]) ^ ((i & 3) << 5));
#pragma unroll
                for (int i = 0; i < 8; i++) mma16816(acc[i], v[i][0], v[i][1], v[i][2], v[i][3], pb0, pb1);
            }
            __syncwarp();
            if (lane == 0) mbar_arrive(bars + B_EMPTY + s * 8);
            if (++s == NSLOT) { s = 0; ph ^= 1; }
        }
        if (tid == 0) TS(3);
        for (; cur < HKV; cur++) flush(cur);
        if (tid == 0) TS(4);
        if (tid == 0) mbar_arrive(bars + B_FREE);
        if (b >= N_FFN_CTA) return;
        {
            uint32_t da[9][10];
#pragma unroll
            for (int i = 0; i < 3; i++) mbar_wait(bars + B_LATE + (9 + 2 * warp + i) * 8, 0);
#pragma unroll
            for (int i = 0; i < 9; i++) {
                const int mt = warp * 9 + i;
                const int c = 2 * (mt & 3) + (mi & 1);
                const uint32_t base = sb + SM_D + (mt >> 2) * SM_DGRP;
                const int r0 = (lane & 7) + (mi >> 1) * 8, r2 = 32 + (lane & 7);
                uint32_t f[4];
                ldsm4t(f, base + r0 * 128 + ((c ^ (r0 & 7)) << 4));
                da[i][0] = f[0]; da[i][1] = f[1]; da[i][2] = f[2]; da[i][3] = f[3];
                ldsm4t(f, base + (r0 + 16) * 128 + ((c ^ (r0 & 7)) << 4));
                da[i][4] = f[0]; da[i][5] = f[1]; da[i][6] = f[2]; da[i][7] = f[3];
                ldsm2t(da[i][8], da[i][9], base + r2 * 128 + ((c ^ (r2 & 7)) << 4));
            }
            if (tid == 0) TS(19);
            bar_sync(3, NCONS + 64);
            const uint32_t* acts = reinterpret_cast<const uint32_t*>(smem + X_ACT);
            const uint32_t b00 = acts[t4], b01 = acts[4 + t4], b10 = acts[8 + t4], b11 = acts[12 + t4], b20 = acts[16 + t4];
            float y[9][4];
#pragma unroll
            for (int i = 0; i < 9; i++) {
                y[i][0] = y[i][1] = y[i][2] = y[i][3] = 0.f;
                mma16816(y[i], da[i][0], da[i][1], da[i][2], da[i][3], b00, b01);
            }
#pragma unroll
            for (int i = 0; i < 9; i++) mma16816(y[i], da[i][4], da[i][5], da[i][6], da[i][7], b10, b11);
#pragma unroll
            for (int i = 0; i < 9; i++) mma1688(y[i], da[i][8], da[i][9], b20);
            uint32_t* row = g_s.y2[b] + warp * 144 + g;
#pragma unroll
            for (int q = 0; q < 3; q++) {
                float r0 = y[4 * q][0], r1 = y[4 * q][2];
#pragma unroll
                for (int j = 1; j < 4; j++) if (4 * q + j < 9 && t4 == j) { r0 = y[4 * q + j][0]; r1 = y[4 * q + j][2]; }
                if (4 * q + t4 < 9) {
                    st_pub1(row + (4 * q + t4) * 16, tagf(r0, tag));
                    st_pub1(row + (4 * q + t4) * 16 + 8, tagf(r1, tag));
                }
            }
            if (tid == 0) TS(16);
        }
        return;
    }

    const int wa = at >> 5;
    auto load_wo = [&]() {
        fence_async_smem();
        mbar_expect_tx(bars + B_WO, 9 * SM_OGRP);
#pragma unroll
        for (int j = 0; j < 9; j++) tma2d(sb + SM_D + j * SM_OGRP, &tmO, j * 64, b * 32, bars + B_WO);
    };
    if (at == 0) TS(5);
    const float x0 = bf_lo(x2pk), x1 = bf_hi(x2pk);
    float mean1, rsd1;
    ln_stats(x0, x1, reinterpret_cast<float*>(smem + X_ST1), at, mean1, rsd1);
    {
        uint32_t fa[8][4];
        float* red0 = reinterpret_cast<float*>(smem + X_RED0);
        float* red1 = reinterpret_cast<float*>(smem + X_RED1);
        if (b < N_MOD_CTA) {
            const uint32_t cpk = pack_bf16(silu_f(bf_lo(c2pk)), silu_f(bf_hi(c2pk)));
            mbar_wait(bars + B_WM + (wa / 3) * 8, 0);
            if (at == 0) TS(20);
            load_frag32(fa, sb + SM_U, wa, lane);
            gemv32(fa, cpk, red0, wa, lane);
            bar_sync(2, NAUX);
            if (at < 32) {
                const float sum = sum9(red0 + at, 32);
                st_pub1(&g_s.mod[b * 32 + at], __float_as_uint(bfr(sum)) | tag);
            }
        }
        if (at == 0) TS(6);
        if (b < N_Q_CTA) {
            mbar_wait(bars + B_WQ + (wa / 3) * 8, 0);
            if (at == 0) TS(21);
            load_frag32(fa, sb + SM_D, wa, lane);
            uint2 sa2, ca2;
            unsigned it = 0;
            do {
                sa2 = ld_poll2(&g_s.mod[2 * at]);
                ca2 = ld_poll2(&g_s.mod[D_MODEL + 2 * at]);
                if (++it > SPIN_MAX) __trap();
            } while (bad2(sa2, tag) | bad2(ca2, tag));
            const uint32_t hpk = modulate2(x0, x1, mean1, rsd1, ca2, sa2);
            if (at == 0) TS(7);
            gemv32(fa, hpk, red1, wa, lane);
            bar_sync(2, NAUX);
            if (at < 32) {
                const float sum = sum9(red1 + at, 32);
                st_pub1(&g_s.q[b * 32 + at], __float_as_uint(bfr(sum)) | tag);
            }
        } else {
            const long long t0 = clock64();
            while (clock64() - t0 < 5000) __nanosleep(200);
        }
    }
    {
        uint2* q_s = reinterpret_cast<uint2*>(smem + SM_Q);
        if (wa < 2) {
            uint4 v0;
            unsigned it = 0;
            do { v0 = ld_poll4(&g_s.q[at * 4]); if (++it > SPIN_MAX) __trap(); } while (bad4(v0, tag));
            q_s[at] = make_uint2((v0.x >> 16) | (v0.y & 0xffff0000u), (v0.z >> 16) | (v0.w & 0xffff0000u));
            __syncwarp();
            if (lane == 0) mbar_arrive(bars + B_QRDY);
        }
        if (at == 0) TS(12);
        if (at == 0 && b < N_JOB_CTA) load_wo();
        {
            const long long t0 = clock64();
            while (clock64() - t0 < Q_DELAY_CLK) __nanosleep(200);
        }
        uint4 v[4];
        unsigned it = 0;
        uint32_t pend = (64 + at + 3 * NAUX < 1024) ? 15u : 7u;
        do {
#pragma unroll
            for (int r = 0; r < 4; r++) if (pend & (1u << r)) v[r] = ld_poll4(&g_s.q[(64 + at + r * NAUX) * 4]);
#pragma unroll
            for (int r = 0; r < 4; r++) if ((pend & (1u << r)) && !bad4(v[r], tag)) pend &= ~(1u << r);
            if (++it > SPIN_MAX) __trap();
            if (pend) __nanosleep(200);
        } while (pend);
#pragma unroll
        for (int r = 0; r < 4; r++) {
            const int idx = 64 + at + r * NAUX;
            if (idx < 1024) q_s[idx] = make_uint2((v[r].x >> 16) | (v[r].y & 0xffff0000u), (v[r].z >> 16) | (v[r].w & 0xffff0000u));
        }
        __syncwarp();
        if (lane == 0) mbar_arrive(bars + B_QALL);
    }
    if (at == 0) TS(8);
    if (b >= N_JOB_CTA) return;
    const int g = lane >> 2, t4 = lane & 3, mi = lane >> 3;
    {
        const int h = b >> 3, sl = b & 7;
        float* jred = reinterpret_cast<float*>(smem + X_RED0);
        float* jml = reinterpret_cast<float*>(smem + X_JML);
        uint32_t oa[8][4];
        mbar_wait_long(bars + B_WO, 0);
#pragma unroll
        for (int mt = 0; mt < 4; mt++) {
#pragma unroll
            for (int ks = 0; ks < 2; ks++) {
                const int r = ks * 16 + (lane & 7) + (mi >> 1) * 8, c = 2 * mt + (mi & 1);
                ldsm4t(oa[mt * 2 + ks], sb + SM_D + wa * SM_OGRP + r * 128 + ((c ^ (r & 7)) << 4));
            }
        }
        if (b < N_FFN_CTA) {
            bar_sync(2, NAUX);
            if (at == 0) {
                fence_async_smem();
                mbar_arrive(bars + B_FREE);
            }
        }
        const int ycol = wa * 64 + t4 * 16 + g;
        uint32_t yp0 = 0, yp1 = 0;
        mbar_wait_long(bars + B_JOB, 0);
        if (h != HKV - 1) {
            const long long t0 = clock64();
            while (clock64() - t0 < JOB_DELAY_CLK) __nanosleep(400);
        }
        if (at == 0) TS(9);
        const int v = at & 7, bl = at >> 3;
        uint4 o4[4];
        uint2 ml[4];
        {
            const uint32_t* pO = &g_s.po[h][sl][0][0];
            const uint32_t* pY = &g_s.y[h > 0 ? h - 1 : 0][sl][ycol];
            uint32_t pend = 0;
#pragma unroll
            for (int r = 0; r < 4; r++) {
                o4[r] = make_uint4(0u, 0u, 0u, 0u); ml[r] = make_uint2(0u, 0x3f800000u);
                if (bl + 36 * r < G) pend |= 1u << r;
            }
            if (h > 0) pend |= 16u;
            unsigned it = 0;
            while (pend) {
#pragma unroll
                for (int r = 0; r < 4; r++) {
                    if (pend & (1u << r)) {
                        o4[r] = ld_poll4(pO + (bl + 36 * r) * PROW + v * 4);
                        ml[r] = ld_poll2(pO + (bl + 36 * r) * PROW + 32);
                    }
                }
                if (pend & 16u) {
                    yp0 = ld_poll1(pY);
                    yp1 = ld_poll1(pY + 8);
                }
#pragma unroll
                for (int r = 0; r < 4; r++)
                    if ((pend & (1u << r)) && !(bad4(o4[r], tag) | bad2(ml[r], tag))) pend &= ~(1u << r);
                if ((pend & 16u) && !(((yp0 ^ tag) | (yp1 ^ tag)) & 3u)) pend &= ~16u;
                if (++it > SPIN_MAX) __trap();
                if (pend && h != HKV - 1) __nanosleep(500);
            }
            __syncwarp();
        }
        if (at == 0) { TS(10); TC(58); }
        float Mw = -3.4e38f;
#pragma unroll
        for (int r = 0; r < 4; r++) if (bl + 36 * r < G) Mw = fmaxf(Mw, untag_bf(ml[r].x));
        Mw = fmaxf(Mw, __shfl_xor_sync(0xffffffffu, Mw, 8));
        Mw = fmaxf(Mw, __shfl_xor_sync(0xffffffffu, Mw, 16));
        float a4[4] = {0.f, 0.f, 0.f, 0.f}, ls = 0.f;
#pragma unroll
        for (int r = 0; r < 4; r++) {
            if (bl + 36 * r < G) {
                const float w = ex2((untag_bf(ml[r].x) - Mw) * LOG2E);
                a4[0] = fmaf(w, __uint_as_float(o4[r].x), a4[0]); a4[1] = fmaf(w, __uint_as_float(o4[r].y), a4[1]);
                a4[2] = fmaf(w, __uint_as_float(o4[r].z), a4[2]); a4[3] = fmaf(w, __uint_as_float(o4[r].w), a4[3]);
                ls = fmaf(w, __uint_as_float(ml[r].y), ls);
            }
        }
#pragma unroll
        for (int o = 8; o < 32; o <<= 1) {
#pragma unroll
            for (int j = 0; j < 4; j++) a4[j] += __shfl_xor_sync(0xffffffffu, a4[j], o);
            ls += __shfl_xor_sync(0xffffffffu, ls, o);
        }
        if (lane < 8) *reinterpret_cast<float4*>(&jred[wa * 32 + lane * 4]) = make_float4(a4[0], a4[1], a4[2], a4[3]);
        if (lane == 0) *reinterpret_cast<float2*>(&jml[wa * 2]) = make_float2(Mw, ls);
        if (at == 0) TC(59);
        bar_sync(2, NAUX);
        if (at == 0) TC(60);
        float2 mlw[9];
        float ow[9];
#pragma unroll
        for (int w = 0; w < 9; w++) { mlw[w] = *reinterpret_cast<const float2*>(&jml[2 * w]); ow[w] = jred[w * 32 + lane]; }
        const float M = fmaxf(fmaxf(fmaxf(fmaxf(mlw[0].x, mlw[1].x), fmaxf(mlw[2].x, mlw[3].x)),
                                    fmaxf(fmaxf(mlw[4].x, mlw[5].x), fmaxf(mlw[6].x, mlw[7].x))), mlw[8].x);
        float oe = 0.f, oo = 0.f, Le = 0.f, Lo = 0.f;
#pragma unroll
        for (int w = 0; w < 9; w++) {
            const float sc = ex2((mlw[w].x - M) * LOG2E);
            if (w & 1) { oo = fmaf(sc, ow[w], oo); Lo = fmaf(sc, mlw[w].y, Lo); }
            else       { oe = fmaf(sc, ow[w], oe); Le = fmaf(sc, mlw[w].y, Le); }
        }
        const float o = __fdividef(oe + oo, Le + Lo);
        if (at == 0) TC(61);
        const uint32_t opk = pack_bf16(o, __shfl_down_sync(0xffffffffu, o, 1));
        const uint32_t b00 = __shfl_sync(0xffffffffu, opk, 2 * t4), b01 = __shfl_sync(0xffffffffu, opk, 8 + 2 * t4);
        const uint32_t b10 = __shfl_sync(0xffffffffu, opk, 16 + 2 * t4), b11 = __shfl_sync(0xffffffffu, opk, 24 + 2 * t4);
        float y[4][4];
#pragma unroll
        for (int mt = 0; mt < 4; mt++) {
            y[mt][0] = y[mt][1] = y[mt][2] = y[mt][3] = 0.f;
            mma16816(y[mt], oa[2 * mt][0], oa[2 * mt][1], oa[2 * mt][2], oa[2 * mt][3], b00, b01);
        }
#pragma unroll
        for (int mt = 0; mt < 4; mt++)
            mma16816(y[mt], oa[2 * mt + 1][0], oa[2 * mt + 1][1], oa[2 * mt + 1][2], oa[2 * mt + 1][3], b10, b11);
        float r0 = y[0][0], r1 = y[0][2];
#pragma unroll
        for (int mt = 1; mt < 4; mt++) if (t4 == mt) { r0 = y[mt][0]; r1 = y[mt][2]; }
        if (h > 0) { r0 += __uint_as_float(yp0); r1 += __uint_as_float(yp1); }
        st_pub1(&g_s.y[h][sl][ycol], tagf(r0, tag));
        st_pub1(&g_s.y[h][sl][ycol + 8], tagf(r1, tag));
        if (at == 0) { TS(11); TC(62); }
    }
    if (b >= N_FFN_CTA) return;

    uint2 ga2, sb2, cb2;
    {
        unsigned it = 0;
        do {
            ga2 = ld_poll2(&g_s.mod[2 * D_MODEL + 2 * at]);
            sb2 = ld_poll2(&g_s.mod[3 * D_MODEL + 2 * at]);
            cb2 = ld_poll2(&g_s.mod[4 * D_MODEL + 2 * at]);
            if (++it > SPIN_MAX) __trap();
        } while (bad2(ga2, tag) | bad2(sb2, tag) | bad2(cb2, tag));
    }
    uint32_t gbv = 0;
    if (b < N_FIN_CTA && at < 8) {
        unsigned it = 0;
        do { gbv = ld_poll1(&g_s.mod[5 * D_MODEL + b * 8 + at]); if (++it > SPIN_MAX) __trap(); } while ((gbv ^ tag) & 3u);
    }
    uint32_t gf[10][4], uf[10][4];
    mbar_wait_long(bars + B_G, 0);
#pragma unroll
    for (int j = 0; j < 5; j++) {
        ldsm4t(gf[2 * j], sb + SM_G + (wa * 64 + lane) * 80 + j * 16);
        ldsm4t(gf[2 * j + 1], sb + SM_G + (wa * 64 + 32 + lane) * 80 + j * 16);
    }
    auto load_u = [&]() {
#pragma unroll
        for (int j = 0; j < 5; j++) {
            ldsm4t(uf[2 * j], sb + SM_U + (wa * 64 + lane) * 80 + j * 16);
            ldsm4t(uf[2 * j + 1], sb + SM_U + (wa * 64 + 32 + lane) * 80 + j * 16);
        }
    };
    mbar_wait_long(bars + B_FREE, 0);
    {
        const long long t0 = clock64();
        while (clock64() - t0 < Y_DELAY_CLK) __nanosleep(100);
    }
    float* x2s = reinterpret_cast<float*>(smem + T_X2);
    float2* tgu = reinterpret_cast<float2*>(smem + T_GU);
    float* tfin = reinterpret_cast<float*>(smem + X_FIN);
    bool have_u = false;
    uint32_t hpk;
    {
        uint2 v[8];
        unsigned it = 0;
        uint32_t pend = 255u;
        const uint32_t* pY = &g_s.y[HKV - 1][0][2 * at];
#pragma unroll
        for (int r = 0; r < 8; r++) v[r] = make_uint2(0u, 0u);
        while (__any_sync(0xffffffffu, pend != 0)) {
#pragma unroll
            for (int r = 0; r < 8; r++) if (pend & (1u << r)) v[r] = ld_poll2(pY + r * D_MODEL);
            if (!have_u && __all_sync(0xffffffffu, mbar_test(bars + B_LATE + wa * 8, 0))) {
                load_u(); have_u = true;
                if (at == 0) TS(22);
            }
#pragma unroll
            for (int r = 0; r < 8; r++) if ((pend & (1u << r)) && !bad2(v[r], tag)) pend &= ~(1u << r);
            if (++it > SPIN_MAX) __trap();
        }
        if (at == 0) { TS(13); TC(48); }
        const float s0 = ((__uint_as_float(v[0].x) + __uint_as_float(v[1].x)) + (__uint_as_float(v[2].x) + __uint_as_float(v[3].x))) +
                         ((__uint_as_float(v[4].x) + __uint_as_float(v[5].x)) + (__uint_as_float(v[6].x) + __uint_as_float(v[7].x)));
        const float s1 = ((__uint_as_float(v[0].y) + __uint_as_float(v[1].y)) + (__uint_as_float(v[2].y) + __uint_as_float(v[3].y))) +
                         ((__uint_as_float(v[4].y) + __uint_as_float(v[5].y)) + (__uint_as_float(v[6].y) + __uint_as_float(v[7].y)));
        const uint32_t apk = pack_bf16(s0, s1);
        const uint32_t gpk = pack_bf16(untag_bf(ga2.x) * bf_lo(apk), untag_bf(ga2.y) * bf_hi(apk));
        const uint32_t ypk = pack_bf16(x0 + bf_lo(gpk), x1 + bf_hi(gpk));
        const float y0 = bf_lo(ypk), y1 = bf_hi(ypk);
        *reinterpret_cast<float2*>(&x2s[2 * at]) = make_float2(y0, y1);
        float mean2, rsd2;
        if (at == 0) TC(49);
        ln_stats(y0, y1, reinterpret_cast<float*>(smem + X_ST2), at, mean2, rsd2);
        if (at == 0) TC(50);
        hpk = modulate2(y0, y1, mean2, rsd2, cb2, sb2);
    }
    if (!have_u) {
        mbar_wait(bars + B_LATE + wa * 8, 0);
        __syncwarp();
        load_u();
        if (at == 0) TS(22);
    }
    if (at == 0) { TS(14); TC(51); }
    {
        float y[5][4];
#pragma unroll
        for (int j = 0; j < 5; j++) y[j][0] = y[j][1] = y[j][2] = y[j][3] = 0.f;
#pragma unroll
        for (int ks = 0; ks < 4; ks++) {
            const uint32_t b0 = __shfl_sync(0xffffffffu, hpk, 8 * ks + t4);
            const uint32_t b1 = __shfl_sync(0xffffffffu, hpk, 8 * ks + 4 + t4);
            const int hf = ks >> 1, e = (ks & 1) * 2;
#pragma unroll
            for (int j = 0; j < 5; j++)
                mma16816(y[j], gf[2 * j + hf][e], uf[2 * j + hf][e], gf[2 * j + hf][e + 1], uf[2 * j + hf][e + 1], b0, b1);
        }
#pragma unroll
        for (int j = 0; j < 5; j++)
            if (t4 == (j & 3)) tgu[wa * FCOLS + j * 8 + g] = make_float2(y[j][0], y[j][2]);
    }
    if (at == 0) TC(52);
    bar_sync(2, NAUX);
    if (at == 0) TC(53);
    if (wa < 2) {
        if (at < FCOLS) {
            float2 p[9];
#pragma unroll
            for (int w = 0; w < 9; w++) p[w] = tgu[w * FCOLS + at];
            const float gs = (((p[0].x + p[1].x) + (p[2].x + p[3].x)) + ((p[4].x + p[5].x) + (p[6].x + p[7].x))) + p[8].x;
            const float us = (((p[0].y + p[1].y) + (p[2].y + p[3].y)) + ((p[4].y + p[5].y) + (p[6].y + p[7].y))) + p[8].y;
            const uint32_t gu = pack_bf16(gs, us);
            const float a = bfr(silu_f(bf_lo(gu))) * bf_hi(gu);
            reinterpret_cast<__nv_bfloat16*>(smem + X_ACT)[at] = __float2bfloat16_rn(a);
        }
        bar_arrive(3, NCONS + 64);
        if (at == 0) { TS(15); TC(54); }
    }
    if (b < N_FIN_CTA) {
        float a4[4] = {0.f, 0.f, 0.f, 0.f};
        {
            const long long t0 = clock64();
            while (clock64() - t0 < F_DELAY_CLK) { }
        }
        if (at < 2 * N_FFN_CTA) {
            const uint32_t* pF = &g_s.y2[at >> 1][b * 8 + (at & 1) * 4];
            uint4 v;
            unsigned it = 0;
            do { v = ld_poll4(pF); if (++it > SPIN_MAX) __trap(); } while (bad4(v, tag));
            a4[0] = __uint_as_float(v.x); a4[1] = __uint_as_float(v.y); a4[2] = __uint_as_float(v.z); a4[3] = __uint_as_float(v.w);
        }
        __syncwarp();
        if (at == 0) { TS(18); TC(55); }
        const bool u1 = lane & 2, u2 = lane & 4;
        float k0 = (u1 ? a4[2] : a4[0]) + __shfl_xor_sync(0xffffffffu, u1 ? a4[0] : a4[2], 2);
        float k1 = (u1 ? a4[3] : a4[1]) + __shfl_xor_sync(0xffffffffu, u1 ? a4[1] : a4[3], 2);
        float k = (u2 ? k1 : k0) + __shfl_xor_sync(0xffffffffu, u2 ? k0 : k1, 4);
        k += __shfl_xor_sync(0xffffffffu, k, 8);
        k += __shfl_xor_sync(0xffffffffu, k, 16);
        if (lane < 8) tfin[wa * 8 + (lane & 1) * 4 + (lane & 2) + ((lane >> 2) & 1)] = k;
        if (at == 0) TC(56);
        bar_sync(2, NAUX);
        if (at < 8) {
            float v[8];
#pragma unroll
            for (int w = 0; w < 8; w++) v[w] = tfin[w * 8 + at];
            const float sum = ((v[0] + v[1]) + (v[2] + v[3])) + ((v[4] + v[5]) + (v[6] + v[7]));
            const float r = x2s[b * 8 + at] + bfr(untag_bf(gbv) * bfr(sum));
            out[b * 8 + at] = __float2bfloat16_rn(r);
        }
        if (at == 0) { TS(17); TC(57); }
    }
    if (b == 0 && at == 0) {
        g_s.ctr[0] = 0u;
        g_s.epoch[0] = (epoch_raw >= 2u) ? 0u : epoch_raw + 1u;
    }
}

typedef CUresult (*EncodeFn)(CUtensorMap*, CUtensorMapDataType, cuuint32_t, void*, const cuuint64_t*, const cuuint64_t*,
                             const cuuint32_t*, const cuuint32_t*, CUtensorMapInterleave, CUtensorMapSwizzle,
                             CUtensorMapL2promotion, CUtensorMapFloatOOBfill);

void make_2d(EncodeFn enc, CUtensorMap* m, void* base, uint64_t cols, uint64_t rows, uint32_t bcols, uint32_t brows,
             CUtensorMapSwizzle sw, CUtensorMapL2promotion pr) {
    cuuint64_t gd[2] = {cols, rows};
    cuuint64_t gs[1] = {cols * 2};
    cuuint32_t bx[2] = {bcols, brows};
    cuuint32_t es[2] = {1, 1};
    enc(m, CU_TENSOR_MAP_DATA_TYPE_BFLOAT16, 2, base, gd, gs, bx, es, CU_TENSOR_MAP_INTERLEAVE_NONE, sw, pr,
        CU_TENSOR_MAP_FLOAT_OOB_FILL_NONE);
}

}

extern "C" void kernel_launch(void* const* d_in, const int* in_sizes, int n_in, void* d_out, int out_size) {
    (void)in_sizes; (void)n_in; (void)out_size;
    static EncodeFn enc = nullptr;
    static int nsm = 0;
    if (!enc) {
        void* fn = nullptr;
        cudaDriverEntryPointQueryResult qr;
        cudaGetDriverEntryPoint("cuTensorMapEncodeTiled", &fn, cudaEnableDefault, &qr);
        enc = (EncodeFn)fn;
        int dev = 0;
        cudaGetDevice(&dev);
        cudaDeviceGetAttribute(&nsm, cudaDevAttrMultiProcessorCount, dev);
        cudaFuncSetAttribute(fused_kernel, cudaFuncAttributeMaxDynamicSharedMemorySize, SM_TOTAL);
    }
    if (!enc) return;

    CUtensorMap tmK, tmV, tmG, tmU, tmM, tmQ, tmO, tmD;
    {
        cuuint64_t gd[3] = {64, 2, (cuuint64_t)HKV * SK};
        cuuint64_t gs[2] = {128, 256};
        cuuint32_t bx[3] = {64, 2, TILE};
        cuuint32_t es[3] = {1, 1, 1};
        enc(&tmK, CU_TENSOR_MAP_DATA_TYPE_BFLOAT16, 3, d_in[1], gd, gs, bx, es, CU_TENSOR_MAP_INTERLEAVE_NONE,
            CU_TENSOR_MAP_SWIZZLE_128B, CU_TENSOR_MAP_L2_PROMOTION_NONE, CU_TENSOR_MAP_FLOAT_OOB_FILL_NONE);
        enc(&tmV, CU_TENSOR_MAP_DATA_TYPE_BFLOAT16, 3, d_in[2], gd, gs, bx, es, CU_TENSOR_MAP_INTERLEAVE_NONE,
            CU_TENSOR_MAP_SWIZZLE_128B, CU_TENSOR_MAP_L2_PROMOTION_NONE, CU_TENSOR_MAP_FLOAT_OOB_FILL_NONE);
    }
    make_2d(enc, &tmG, d_in[6], FF, D_MODEL, FCOLS, 192, CU_TENSOR_MAP_SWIZZLE_NONE, CU_TENSOR_MAP_L2_PROMOTION_L2_256B);
    make_2d(enc, &tmU, d_in[7], FF, D_MODEL, FCOLS, 64, CU_TENSOR_MAP_SWIZZLE_NONE, CU_TENSOR_MAP_L2_PROMOTION_L2_256B);
    make_2d(enc, &tmM, d_in[10], 6 * D_MODEL, D_MODEL, 32, 192, CU_TENSOR_MAP_SWIZZLE_64B, CU_TENSOR_MAP_L2_PROMOTION_L2_128B);
    make_2d(enc, &tmQ, d_in[3], 4096, D_MODEL, 32, 192, CU_TENSOR_MAP_SWIZZLE_64B, CU_TENSOR_MAP_L2_PROMOTION_L2_128B);
    make_2d(enc, &tmO, d_in[4], D_MODEL, 4096, 64, 32, CU_TENSOR_MAP_SWIZZLE_128B, CU_TENSOR_MAP_L2_PROMOTION_NONE);
    make_2d(enc, &tmD, d_in[8], D_MODEL, FF, 64, FCOLS, CU_TENSOR_MAP_SWIZZLE_128B, CU_TENSOR_MAP_L2_PROMOTION_NONE);

    int grid = nsm < MAXG ? nsm : MAXG;
    if (grid < N_JOB_CTA) return;
    fused_kernel<<<grid, NTHREADS, SM_TOTAL, cudaStreamPerThread>>>(
        tmK, tmV, tmG, tmU, tmM, tmQ, tmO, tmD, (const __nv_bfloat16*)d_in[0], (const __nv_bfloat16*)d_in[9],
        (__nv_bfloat16*)d_out);
}
```
